```python
import torch

def _softmax(x, axis=-1):
    return torch.softmax(x, dim=axis)

def _gelu(x):
    return torch.nn.functional.gelu(x, approximate='tanh')

def _silu(x):
    return torch.nn.functional.silu(x)

def _sigmoid(x):
    return torch.sigmoid(x)

def _layernorm(x, axis=-1, eps=1e-05):
    m = x.mean(dim=axis, keepdim=True)
    v = x.var(dim=axis, keepdim=True, unbiased=False)
    return (x - m) / torch.sqrt(v + eps)

def _scatter_add(tgt, idx, src, axis=0):
    return tgt.clone().index_add_(axis, idx, src)

def _segment_sum(src, seg, n):
    out = torch.zeros((n,) + src.shape[1:], dtype=src.dtype)
    return out.index_add_(0, seg, src)

def _pad(x, pw):
    flat = tuple((v for pair in reversed(pw) for v in pair))
    return torch.nn.functional.pad(x, flat)
kernel_name = 'concat_heads__sliding_local_dilated__memory_aug_recurrent_mem_tr__prompt'

def setup_inputs():

    _w = lambda a: (lambda t: t.to(torch.bfloat16) if t.is_floating_point() else t)(torch.as_tensor(a))

    def _A_setup():
        B, S, D = (1, 2048, 448)
        return {'x': _w((lambda *s: torch.randn(*s, dtype=torch.bfloat16) * 0.2)(B, S, D)), 'wqkv': _w((lambda *s: torch.randn(*s, dtype=torch.bfloat16) * 0.2)(D, 3 * D)), 'wo': _w((lambda *s: torch.randn(*s, dtype=torch.bfloat16) * 0.05)(D, D))}
    _A_in = _A_setup()

    def _B_setup():
        B, S, Dm = (1, 2048, 448)
        H, Dh = (16, 256)
        M, seg = (8, 32)
        seg = min(seg, S)
        S = S // seg * seg
        return {'x': _w((lambda *s: torch.randn(*s, dtype=torch.bfloat16) * 0.05)(B, S, Dm)), 'mem0': _w((lambda *s: torch.randn(*s, dtype=torch.bfloat16) * 1.6)(B, M, Dm)), 'Wq': _w((lambda *s: torch.randn(*s, dtype=torch.bfloat16) * 0.8)(Dm, H, Dh) * Dm ** (-0.5)), 'Wk': _w((lambda *s: torch.randn(*s, dtype=torch.bfloat16) * 0.8)(Dm, H, Dh) * Dm ** (-0.5)), 'Wv': _w((lambda *s: torch.randn(*s, dtype=torch.bfloat16) * 1.6)(Dm, H, Dh) * Dm ** (-0.5)), 'Wo': _w((lambda *s: torch.randn(*s, dtype=torch.bfloat16) * 1.6)(H, Dh, Dm) * (H * Dh) ** (-0.5)), 'seg_len': seg}
    _B_in = _B_setup()
    return {'A_x': _A_in['x'], 'A_wqkv': _A_in['wqkv'], 'A_wo': _A_in['wo'], 'B_x': _B_in['x'], 'B_mem0': _B_in['mem0'], 'B_Wq': _B_in['Wq'], 'B_Wk': _B_in['Wk'], 'B_Wv': _B_in['Wv'], 'B_Wo': _B_in['Wo'], 'B_seg_len': _B_in['seg_len']}

def reference(A_x, A_wqkv, A_wo, B_x, B_mem0, B_Wq, B_Wk, B_Wv, B_Wo, B_seg_len):

    def _A_ref(x, wqkv, wo):
        B, S, D = x.shape
        H = 16
        Dh = D // H
        W, dil = (8, 2)
        qkv = (lambda x, *d: x.permute(*d))((x @ wqkv).reshape(B, S, 3, H, Dh), 2, 0, 3, 1, 4)
        q, k, v = (qkv[0], qkv[1], qkv[2])
        scale = Dh ** (-0.5)
        pos = torch.arange(S)
        off = torch.arange(W) * dil
        idx = pos[:, None] - off[None, :]
        mask = idx >= 0
        idx_c = torch.where(mask, idx, 0).reshape(-1)
        kg = k[:, :, idx_c, :].reshape(B, H, S, W, Dh)
        vg = v[:, :, idx_c, :].reshape(B, H, S, W, Dh)
        logits = torch.einsum('bhsd,bhswd->bhsw', q, kg) * scale
        logits = torch.where(mask[None, None, :, :], logits, -1000000000.0)
        attn = _softmax(logits, axis=-1)
        o = torch.einsum('bhsw,bhswd->bhsd', attn, vg)
        return (lambda x, *d: x.permute(*d))(o, 0, 2, 1, 3).reshape(B, S, D) @ wo

    def _B_ref(x, mem0, Wq, Wk, Wv, Wo, seg_len):
        B, S, Dm = x.shape
        H, Dh = (Wq.shape[1], Wq.shape[2])
        M = mem0.shape[1]
        scale = Dh ** (-0.5)
        n_seg = S // seg_len
        L = M + seg_len
        idx = torch.arange(L)
        mask = (idx[:, None] < M) | (idx[:, None] >= idx[None, :])
        mem = mem0
        outs = []
        for s in range(n_seg):
            xs = x[:, s * seg_len:(s + 1) * seg_len, :].clone()
            h = torch.concatenate([mem, xs], axis=1)
            q = torch.einsum('btd,dhe->bhte', h, Wq)
            k = torch.einsum('btd,dhe->bhte', h, Wk)
            v = torch.einsum('btd,dhe->bhte', h, Wv)
            scores = torch.einsum('bhqe,bhke->bhqk', q, k) * scale
            scores = torch.where(mask[None, None], scores, -1000000000.0)
            p = _softmax(scores, axis=-1)
            o = torch.einsum('bhqk,bhke->bhqe', p, v)
            o = torch.einsum('bhte,hed->btd', o, Wo)
            mem = o[:, :M, :].clone()
            outs.append(o[:, M:, :])
        return torch.concatenate(outs, axis=1)
    a = _A_ref(A_x, A_wqkv, A_wo)
    b = _B_ref(B_x, B_mem0, B_Wq, B_Wk, B_Wv, B_Wo, B_seg_len)
    return torch.concatenate([a, b], axis=-1)
```

```cpp
#include <cuda_runtime.h>
#include <cuda_bf16.h>
#include <cuda.h>
#include <stdint.h>
#define DEVI __device__ __forceinline__
typedef __nv_bfloat16 bf16;

DEVI uint32_t smem_u32(const void* p) { return (uint32_t)__cvta_generic_to_shared(p); }
DEVI uint32_t mapa(uint32_t a, uint32_t r) { uint32_t o; asm("mapa.shared::cluster.u32 %0, %1, %2;" : "=r"(o) : "r"(a), "r"(r)); return o; }
DEVI unsigned clk32() { unsigned c; asm volatile("mov.u32 %0, %%clock;" : "=r"(c) :: "memory"); return c; }
DEVI void mbar_init(uint32_t bar, uint32_t n) { asm volatile("mbarrier.init.shared::cta.b64 [%0], %1;" :: "r"(bar), "r"(n) : "memory"); }
DEVI void mbar_arrive(uint32_t bar) { asm volatile("mbarrier.arrive.shared::cta.b64 _, [%0];" :: "r"(bar) : "memory"); }
DEVI void mbar_arrive_remote(uint32_t bar) { asm volatile("mbarrier.arrive.relaxed.cluster.shared::cluster.b64 _, [%0];" :: "r"(bar) : "memory"); }
#define SPIN_LIMIT 2000000
DEVI void mbar_wait(uint32_t bar, uint32_t par) {
  asm volatile("{\n.reg .pred p;\n.reg .u32 c;\nmbarrier.try_wait.parity.shared::cta.b64 p, [%0], %1;\n@p bra LD;\nmov.u32 c, 0;\nLW:\n"
               "mbarrier.try_wait.parity.shared::cta.b64 p, [%0], %1;\n@p bra LD;\nadd.u32 c, c, 1;\nsetp.lt.u32 p, c, 400000;\n@p bra LW;\ntrap;\nLD:\n}" :: "r"(bar), "r"(par) : "memory");
}
template <int ID, int N> DEVI void bar_sync() { asm volatile("bar.sync %0, %1;" :: "n"(ID), "n"(N) : "memory"); }
template <int ID, int N> DEVI void bar_arrive() { asm volatile("bar.arrive %0, %1;" :: "n"(ID), "n"(N) : "memory"); }
DEVI void bar_sync_id(int id, int n) { asm volatile("bar.sync %0, %1;" :: "r"(id), "r"(n) : "memory"); }
DEVI void fence_async_smem() { asm volatile("fence.proxy.async.shared::cta;" ::: "memory"); }
DEVI void fence_async_global() { asm volatile("fence.proxy.async.global;" ::: "memory"); }
DEVI void mma16816(float* c, uint32_t a0, uint32_t a1, uint32_t a2, uint32_t a3, uint32_t b0, uint32_t b1) {
  asm volatile("mma.sync.aligned.m16n8k16.row.col.f32.bf16.bf16.f32 {%0,%1,%2,%3}, {%4,%5,%6,%7}, {%8,%9}, {%0,%1,%2,%3};"
    : "+f"(c[0]), "+f"(c[1]), "+f"(c[2]), "+f"(c[3]) : "r"(a0), "r"(a1), "r"(a2), "r"(a3), "r"(b0), "r"(b1));
}
DEVI void mma16816z(float* c, uint32_t a0, uint32_t a1, uint32_t a2, uint32_t a3, uint32_t b0, uint32_t b1) {
  asm volatile("mma.sync.aligned.m16n8k16.row.col.f32.bf16.bf16.f32 {%0,%1,%2,%3}, {%4,%5,%6,%7}, {%8,%9}, {%10,%10,%10,%10};"
    : "=f"(c[0]), "=f"(c[1]), "=f"(c[2]), "=f"(c[3]) : "r"(a0), "r"(a1), "r"(a2), "r"(a3), "r"(b0), "r"(b1), "f"(0.f));
}
DEVI void mma1688(float* c, uint32_t a0, uint32_t a1, uint32_t b0) {
  asm volatile("mma.sync.aligned.m16n8k8.row.col.f32.bf16.bf16.f32 {%0,%1,%2,%3}, {%4,%5}, {%6}, {%0,%1,%2,%3};"
    : "+f"(c[0]), "+f"(c[1]), "+f"(c[2]), "+f"(c[3]) : "r"(a0), "r"(a1), "r"(b0));
}
DEVI void ldsm4(uint32_t a, uint32_t& r0, uint32_t& r1, uint32_t& r2, uint32_t& r3) { asm volatile("ldmatrix.sync.aligned.m8n8.x4.shared.b16 {%0,%1,%2,%3}, [%4];" : "=r"(r0), "=r"(r1), "=r"(r2), "=r"(r3) : "r"(a) : "memory"); }
DEVI void ldsm2(uint32_t a, uint32_t& r0, uint32_t& r1) { asm volatile("ldmatrix.sync.aligned.m8n8.x2.shared.b16 {%0,%1}, [%2];" : "=r"(r0), "=r"(r1) : "r"(a) : "memory"); }
DEVI void ldsm4t(uint32_t a, uint32_t& r0, uint32_t& r1, uint32_t& r2, uint32_t& r3) { asm volatile("ldmatrix.sync.aligned.m8n8.x4.trans.shared.b16 {%0,%1,%2,%3}, [%4];" : "=r"(r0), "=r"(r1), "=r"(r2), "=r"(r3) : "r"(a) : "memory"); }
DEVI void ldsm2t(uint32_t a, uint32_t& r0, uint32_t& r1) { asm volatile("ldmatrix.sync.aligned.m8n8.x2.trans.shared.b16 {%0,%1}, [%2];" : "=r"(r0), "=r"(r1) : "r"(a) : "memory"); }
DEVI void stsm4(uint32_t a, uint32_t r0, uint32_t r1, uint32_t r2, uint32_t r3) { asm volatile("stmatrix.sync.aligned.m8n8.x4.shared.b16 [%0], {%1,%2,%3,%4};" :: "r"(a), "r"(r0), "r"(r1), "r"(r2), "r"(r3) : "memory"); }
DEVI void stsm2(uint32_t a, uint32_t r0, uint32_t r1) { asm volatile("stmatrix.sync.aligned.m8n8.x2.shared.b16 [%0], {%1,%2};" :: "r"(a), "r"(r0), "r"(r1) : "memory"); }
DEVI void stsm4t(uint32_t a, uint32_t r0, uint32_t r1, uint32_t r2, uint32_t r3) { asm volatile("stmatrix.sync.aligned.m8n8.x4.trans.shared.b16 [%0], {%1,%2,%3,%4};" :: "r"(a), "r"(r0), "r"(r1), "r"(r2), "r"(r3) : "memory"); }
DEVI uint32_t movm(uint32_t a) { uint32_t d; asm volatile("movmatrix.sync.aligned.m8n8.trans.b16 %0, %1;" : "=r"(d) : "r"(a)); return d; }
DEVI uint32_t pack_bf(float lo, float hi) { uint32_t d; asm("cvt.rn.bf16x2.f32 %0, %1, %2;" : "=r"(d) : "f"(hi), "f"(lo)); return d; }
DEVI float bf_lo(uint32_t v) { return __uint_as_float(v << 16); }
DEVI float bf_hi(uint32_t v) { return __uint_as_float(v & 0xffff0000u); }
DEVI float ex2(float x) { float y; asm("ex2.approx.ftz.f32 %0, %1;" : "=f"(y) : "f"(x)); return y; }
DEVI float rcpf(float x) { float y; asm("rcp.approx.ftz.f32 %0, %1;" : "=f"(y) : "f"(x)); return y; }
DEVI uint4 lds128(uint32_t a) { uint4 v; asm volatile("ld.shared.v4.u32 {%0,%1,%2,%3}, [%4];" : "=r"(v.x), "=r"(v.y), "=r"(v.z), "=r"(v.w) : "r"(a) : "memory"); return v; }
DEVI uint2 lds64(uint32_t a) { uint2 v; asm volatile("ld.shared.v2.u32 {%0,%1}, [%2];" : "=r"(v.x), "=r"(v.y) : "r"(a) : "memory"); return v; }
DEVI uint32_t lds32(uint32_t a) { uint32_t v; asm volatile("ld.shared.u32 %0, [%1];" : "=r"(v) : "r"(a) : "memory"); return v; }
DEVI void sts32(uint32_t a, uint32_t v) { asm volatile("st.shared.u32 [%0], %1;" :: "r"(a), "r"(v) : "memory"); }
DEVI void sts64(uint32_t a, uint32_t x, uint32_t y) { asm volatile("st.shared.v2.u32 [%0], {%1,%2};" :: "r"(a), "r"(x), "r"(y) : "memory"); }
DEVI void sts64f(uint32_t a, float x, float y) { asm volatile("st.shared.v2.f32 [%0], {%1,%2};" :: "r"(a), "f"(x), "f"(y) : "memory"); }
DEVI void sts128(uint32_t a, uint4 v) { asm volatile("st.shared.v4.u32 [%0], {%1,%2,%3,%4};" :: "r"(a), "r"(v.x), "r"(v.y), "r"(v.z), "r"(v.w) : "memory"); }
DEVI uint4 ldg128_relaxed(const void* p) { uint4 v; asm volatile("{.reg .b128 t; ld.relaxed.gpu.global.b128 t, [%2]; mov.b128 {%0,%1}, t;}" : "=l"(*(unsigned long long*)&v.x), "=l"(*(unsigned long long*)&v.z) : "l"(p) : "memory"); return v; }
DEVI unsigned ldg_relaxed(const unsigned* p) { unsigned v; asm volatile("ld.relaxed.gpu.global.u32 %0, [%1];" : "=r"(v) : "l"(p) : "memory"); return v; }
DEVI void wait_flag(const unsigned* p, unsigned target) { int spin = 0; while (__any_sync(0xffffffffu, ldg_relaxed(p) < target)) { if (++spin > SPIN_LIMIT) __trap(); } }
template <int N> DEVI void bulk_wait() { asm volatile("cp.async.bulk.wait_group %0;" :: "n"(N) : "memory"); }
#define ELECT "{.reg .pred pe; elect.sync _|pe, 0xffffffff;\n"
DEVI void e_expect(uint32_t bar, uint32_t tx) { asm volatile(ELECT "@pe mbarrier.arrive.expect_tx.shared::cta.b64 _, [%0], %1;}" :: "r"(bar), "r"(tx) : "memory"); }
DEVI void e_arrive(uint32_t bar) { asm volatile(ELECT "@pe mbarrier.arrive.shared::cta.b64 _, [%0];}" :: "r"(bar) : "memory"); }
DEVI void e_g2s(uint32_t dst, const void* src, uint32_t bytes, uint32_t bar) { asm volatile(ELECT "@pe cp.async.bulk.shared::cluster.global.mbarrier::complete_tx::bytes [%0], [%1], %2, [%3];}" :: "r"(dst), "l"(src), "r"(bytes), "r"(bar) : "memory"); }
DEVI void e_s2c(uint32_t dst, uint32_t src, uint32_t bytes, uint32_t bar) { asm volatile(ELECT "@pe cp.async.bulk.shared::cluster.shared::cta.mbarrier::complete_tx::bytes [%0], [%1], %2, [%3];}" :: "r"(dst), "r"(src), "r"(bytes), "r"(bar) : "memory"); }
DEVI void e_s2g_commit(void* dst, uint32_t src, uint32_t bytes) { asm volatile(ELECT "@pe cp.async.bulk.global.shared::cta.bulk_group [%0], [%1], %2;\n@pe cp.async.bulk.commit_group;}" :: "l"(dst), "r"(src), "r"(bytes) : "memory"); }
DEVI void e_tma3d_mc(uint32_t dst, const CUtensorMap* m, int c0, int c1, int c2, uint32_t bar, uint16_t mask) {
  asm volatile(ELECT "@pe cp.async.bulk.tensor.3d.shared::cluster.global.mbarrier::complete_tx::bytes.multicast::cluster [%0], [%1, {%2,%3,%4}], [%5], %6;}" :: "r"(dst), "l"(m), "r"(c0), "r"(c1), "r"(c2), "r"(bar), "h"(mask) : "memory");
}
DEVI void e_tma3d(uint32_t dst, const CUtensorMap* m, int c0, int c1, int c2, uint32_t bar) {
  asm volatile(ELECT "@pe cp.async.bulk.tensor.3d.shared::cluster.global.mbarrier::complete_tx::bytes [%0], [%1, {%2,%3,%4}], [%5];}" :: "r"(dst), "l"(m), "r"(c0), "r"(c1), "r"(c2), "r"(bar) : "memory");
}
DEVI void e_tma2d(uint32_t dst, const CUtensorMap* m, int c0, int c1, uint32_t bar) {
  asm volatile(ELECT "@pe cp.async.bulk.tensor.2d.shared::cluster.global.mbarrier::complete_tx::bytes [%0], [%1, {%2,%3}], [%4];}" :: "r"(dst), "l"(m), "r"(c0), "r"(c1), "r"(bar) : "memory");
}
DEVI void e_red_add(unsigned* p, unsigned v) { asm volatile(ELECT "@pe red.relaxed.gpu.global.add.u32 [%0], %1;}" :: "l"(p), "r"(v) : "memory"); }
DEVI void wg_fence() { asm volatile("wgmma.fence.sync.aligned;" ::: "memory"); }
DEVI void wg_commit() { asm volatile("wgmma.commit_group.sync.aligned;" ::: "memory"); }
template <int N> DEVI void wg_wait() { asm volatile("wgmma.wait_group.sync.aligned %0;" :: "n"(N) : "memory"); }
template <int N> DEVI void acc_fence(float* d) {
  #pragma unroll
  for (int i = 0; i < N; i++) asm volatile("" : "+f"(d[i]) :: "memory");
}
DEVI void cluster_sync_full() { asm volatile("barrier.cluster.arrive.aligned; barrier.cluster.wait.aligned;" ::: "memory"); }
DEVI void cluster_sync_relaxed() { asm volatile("barrier.cluster.arrive.relaxed.aligned; barrier.cluster.wait.aligned;" ::: "memory"); }
DEVI uint64_t mkdesc(uint32_t addr, uint32_t lbo, uint32_t sbo, uint32_t swz) {
  return (uint64_t)((addr & 0x3FFFF) >> 4) | ((uint64_t)(lbo >> 4) << 16) | ((uint64_t)(sbo >> 4) << 32) | ((uint64_t)swz << 62);
}
#define OPAQUE(x) asm volatile("" : "+r"(x))

constexpr int D = 448, NH = 16, SL = 112, SEG = 32, NSEG = 64, SEQ = 2048, OUTW = 896;
__device__ uint4 g_frag[2][NH * 28 * 28 * 32];
__device__ __align__(1024) bf16 g_kt[(size_t)NSEG * NH * 8 * D * 8];
__device__ __align__(1024) bf16 g_vt[(size_t)NSEG * NH * 5 * D * 8];
__device__ __align__(16384) char g_acc[35 * 16384];
__device__ __align__(128) unsigned g_flag[NSEG * NH * 4 + NSEG + 64];
template <int TB> DEVI void wg_rs32(float* d, const uint32_t* a, uint64_t db) {
  asm volatile("wgmma.mma_async.sync.aligned.m64n32k16.f32.bf16.bf16 {%0,%1,%2,%3,%4,%5,%6,%7,%8,%9,%10,%11,%12,%13,%14,%15}, {%16,%17,%18,%19}, %20, 1, 1, 1, %21;"
    : "+f"(d[0]), "+f"(d[1]), "+f"(d[2]), "+f"(d[3]), "+f"(d[4]), "+f"(d[5]), "+f"(d[6]), "+f"(d[7]), "+f"(d[8]), "+f"(d[9]), "+f"(d[10]), "+f"(d[11]), "+f"(d[12]), "+f"(d[13]), "+f"(d[14]), "+f"(d[15])
    : "r"(a[0]), "r"(a[1]), "r"(a[2]), "r"(a[3]), "l"(db), "n"(TB));
}
template <int TB> DEVI void wg_rs32z(float* d, const uint32_t* a, uint64_t db) {
  asm volatile("wgmma.mma_async.sync.aligned.m64n32k16.f32.bf16.bf16 {%0,%1,%2,%3,%4,%5,%6,%7,%8,%9,%10,%11,%12,%13,%14,%15}, {%16,%17,%18,%19}, %20, 0, 1, 1, %21;"
    : "=f"(d[0]), "=f"(d[1]), "=f"(d[2]), "=f"(d[3]), "=f"(d[4]), "=f"(d[5]), "=f"(d[6]), "=f"(d[7]), "=f"(d[8]), "=f"(d[9]), "=f"(d[10]), "=f"(d[11]), "=f"(d[12]), "=f"(d[13]), "=f"(d[14]), "=f"(d[15])
    : "r"(a[0]), "r"(a[1]), "r"(a[2]), "r"(a[3]), "l"(db), "n"(TB));
}
template <int TA, int TB> DEVI void wg_ss32(float* d, uint64_t da, uint64_t db) {
  asm volatile("wgmma.mma_async.sync.aligned.m64n32k16.f32.bf16.bf16 {%0,%1,%2,%3,%4,%5,%6,%7,%8,%9,%10,%11,%12,%13,%14,%15}, %16, %17, 1, 1, 1, %18, %19;"
    : "+f"(d[0]), "+f"(d[1]), "+f"(d[2]), "+f"(d[3]), "+f"(d[4]), "+f"(d[5]), "+f"(d[6]), "+f"(d[7]), "+f"(d[8]), "+f"(d[9]), "+f"(d[10]), "+f"(d[11]), "+f"(d[12]), "+f"(d[13]), "+f"(d[14]), "+f"(d[15])
    : "l"(da), "l"(db), "n"(TA), "n"(TB));
}
template <int TA, int TB> DEVI void wg_ss32z(float* d, uint64_t da, uint64_t db) {
  asm volatile("wgmma.mma_async.sync.aligned.m64n32k16.f32.bf16.bf16 {%0,%1,%2,%3,%4,%5,%6,%7,%8,%9,%10,%11,%12,%13,%14,%15}, %16, %17, 0, 1, 1, %18, %19;"
    : "=f"(d[0]), "=f"(d[1]), "=f"(d[2]), "=f"(d[3]), "=f"(d[4]), "=f"(d[5]), "=f"(d[6]), "=f"(d[7]), "=f"(d[8]), "=f"(d[9]), "=f"(d[10]), "=f"(d[11]), "=f"(d[12]), "=f"(d[13]), "=f"(d[14]), "=f"(d[15])
    : "l"(da), "l"(db), "n"(TA), "n"(TB));
}
template <int TA, int TB> DEVI void wg_ss112(float* d, uint64_t da, uint64_t db) {
  asm volatile("wgmma.mma_async.sync.aligned.m64n112k16.f32.bf16.bf16 {%0,%1,%2,%3,%4,%5,%6,%7,%8,%9,%10,%11,%12,%13,%14,%15,%16,%17,%18,%19,%20,%21,%22,%23,%24,%25,%26,%27,%28,%29,%30,%31,%32,%33,%34,%35,%36,%37,%38,%39,%40,%41,%42,%43,%44,%45,%46,%47,%48,%49,%50,%51,%52,%53,%54,%55}, %56, %57, 1, 1, 1, %58, %59;"
    : "+f"(d[0]), "+f"(d[1]), "+f"(d[2]), "+f"(d[3]), "+f"(d[4]), "+f"(d[5]), "+f"(d[6]), "+f"(d[7]), "+f"(d[8]), "+f"(d[9]), "+f"(d[10]), "+f"(d[11]), "+f"(d[12]), "+f"(d[13]), "+f"(d[14]), "+f"(d[15]), "+f"(d[16]), "+f"(d[17]), "+f"(d[18]), "+f"(d[19]), "+f"(d[20]), "+f"(d[21]), "+f"(d[22]), "+f"(d[23]), "+f"(d[24]), "+f"(d[25]), "+f"(d[26]), "+f"(d[27]), "+f"(d[28]), "+f"(d[29]), "+f"(d[30]), "+f"(d[31]), "+f"(d[32]), "+f"(d[33]), "+f"(d[34]), "+f"(d[35]), "+f"(d[36]), "+f"(d[37]), "+f"(d[38]), "+f"(d[39]), "+f"(d[40]), "+f"(d[41]), "+f"(d[42]), "+f"(d[43]), "+f"(d[44]), "+f"(d[45]), "+f"(d[46]), "+f"(d[47]), "+f"(d[48]), "+f"(d[49]), "+f"(d[50]), "+f"(d[51]), "+f"(d[52]), "+f"(d[53]), "+f"(d[54]), "+f"(d[55])
    : "l"(da), "l"(db), "n"(TA), "n"(TB));
}
template <int TA, int TB> DEVI void wg_ss112z(float* d, uint64_t da, uint64_t db) {
  asm volatile("wgmma.mma_async.sync.aligned.m64n112k16.f32.bf16.bf16 {%0,%1,%2,%3,%4,%5,%6,%7,%8,%9,%10,%11,%12,%13,%14,%15,%16,%17,%18,%19,%20,%21,%22,%23,%24,%25,%26,%27,%28,%29,%30,%31,%32,%33,%34,%35,%36,%37,%38,%39,%40,%41,%42,%43,%44,%45,%46,%47,%48,%49,%50,%51,%52,%53,%54,%55}, %56, %57, 0, 1, 1, %58, %59;"
    : "=f"(d[0]), "=f"(d[1]), "=f"(d[2]), "=f"(d[3]), "=f"(d[4]), "=f"(d[5]), "=f"(d[6]), "=f"(d[7]), "=f"(d[8]), "=f"(d[9]), "=f"(d[10]), "=f"(d[11]), "=f"(d[12]), "=f"(d[13]), "=f"(d[14]), "=f"(d[15]), "=f"(d[16]), "=f"(d[17]), "=f"(d[18]), "=f"(d[19]), "=f"(d[20]), "=f"(d[21]), "=f"(d[22]), "=f"(d[23]), "=f"(d[24]), "=f"(d[25]), "=f"(d[26]), "=f"(d[27]), "=f"(d[28]), "=f"(d[29]), "=f"(d[30]), "=f"(d[31]), "=f"(d[32]), "=f"(d[33]), "=f"(d[34]), "=f"(d[35]), "=f"(d[36]), "=f"(d[37]), "=f"(d[38]), "=f"(d[39]), "=f"(d[40]), "=f"(d[41]), "=f"(d[42]), "=f"(d[43]), "=f"(d[44]), "=f"(d[45]), "=f"(d[46]), "=f"(d[47]), "=f"(d[48]), "=f"(d[49]), "=f"(d[50]), "=f"(d[51]), "=f"(d[52]), "=f"(d[53]), "=f"(d[54]), "=f"(d[55])
    : "l"(da), "l"(db), "n"(TA), "n"(TB));
}
template <int TB> DEVI void wg_rs112(float* d, const uint32_t* a, uint64_t db) {
  asm volatile("wgmma.mma_async.sync.aligned.m64n112k16.f32.bf16.bf16 {%0,%1,%2,%3,%4,%5,%6,%7,%8,%9,%10,%11,%12,%13,%14,%15,%16,%17,%18,%19,%20,%21,%22,%23,%24,%25,%26,%27,%28,%29,%30,%31,%32,%33,%34,%35,%36,%37,%38,%39,%40,%41,%42,%43,%44,%45,%46,%47,%48,%49,%50,%51,%52,%53,%54,%55}, {%56,%57,%58,%59}, %60, 1, 1, 1, %61;"
    : "+f"(d[0]), "+f"(d[1]), "+f"(d[2]), "+f"(d[3]), "+f"(d[4]), "+f"(d[5]), "+f"(d[6]), "+f"(d[7]), "+f"(d[8]), "+f"(d[9]), "+f"(d[10]), "+f"(d[11]), "+f"(d[12]), "+f"(d[13]), "+f"(d[14]), "+f"(d[15]), "+f"(d[16]), "+f"(d[17]), "+f"(d[18]), "+f"(d[19]), "+f"(d[20]), "+f"(d[21]), "+f"(d[22]), "+f"(d[23]), "+f"(d[24]), "+f"(d[25]), "+f"(d[26]), "+f"(d[27]), "+f"(d[28]), "+f"(d[29]), "+f"(d[30]), "+f"(d[31]), "+f"(d[32]), "+f"(d[33]), "+f"(d[34]), "+f"(d[35]), "+f"(d[36]), "+f"(d[37]), "+f"(d[38]), "+f"(d[39]), "+f"(d[40]), "+f"(d[41]), "+f"(d[42]), "+f"(d[43]), "+f"(d[44]), "+f"(d[45]), "+f"(d[46]), "+f"(d[47]), "+f"(d[48]), "+f"(d[49]), "+f"(d[50]), "+f"(d[51]), "+f"(d[52]), "+f"(d[53]), "+f"(d[54]), "+f"(d[55])
    : "r"(a[0]), "r"(a[1]), "r"(a[2]), "r"(a[3]), "l"(db), "n"(TB));
}
template <int TB> DEVI void wg_rs112z(float* d, const uint32_t* a, uint64_t db) {
  asm volatile("wgmma.mma_async.sync.aligned.m64n112k16.f32.bf16.bf16 {%0,%1,%2,%3,%4,%5,%6,%7,%8,%9,%10,%11,%12,%13,%14,%15,%16,%17,%18,%19,%20,%21,%22,%23,%24,%25,%26,%27,%28,%29,%30,%31,%32,%33,%34,%35,%36,%37,%38,%39,%40,%41,%42,%43,%44,%45,%46,%47,%48,%49,%50,%51,%52,%53,%54,%55}, {%56,%57,%58,%59}, %60, 0, 1, 1, %61;"
    : "=f"(d[0]), "=f"(d[1]), "=f"(d[2]), "=f"(d[3]), "=f"(d[4]), "=f"(d[5]), "=f"(d[6]), "=f"(d[7]), "=f"(d[8]), "=f"(d[9]), "=f"(d[10]), "=f"(d[11]), "=f"(d[12]), "=f"(d[13]), "=f"(d[14]), "=f"(d[15]), "=f"(d[16]), "=f"(d[17]), "=f"(d[18]), "=f"(d[19]), "=f"(d[20]), "=f"(d[21]), "=f"(d[22]), "=f"(d[23]), "=f"(d[24]), "=f"(d[25]), "=f"(d[26]), "=f"(d[27]), "=f"(d[28]), "=f"(d[29]), "=f"(d[30]), "=f"(d[31]), "=f"(d[32]), "=f"(d[33]), "=f"(d[34]), "=f"(d[35]), "=f"(d[36]), "=f"(d[37]), "=f"(d[38]), "=f"(d[39]), "=f"(d[40]), "=f"(d[41]), "=f"(d[42]), "=f"(d[43]), "=f"(d[44]), "=f"(d[45]), "=f"(d[46]), "=f"(d[47]), "=f"(d[48]), "=f"(d[49]), "=f"(d[50]), "=f"(d[51]), "=f"(d[52]), "=f"(d[53]), "=f"(d[54]), "=f"(d[55])
    : "r"(a[0]), "r"(a[1]), "r"(a[2]), "r"(a[3]), "l"(db), "n"(TB));
}
template <int TA, int TB> DEVI void wg_ss128(float* d, uint64_t da, uint64_t db) {
  asm volatile("wgmma.mma_async.sync.aligned.m64n128k16.f32.bf16.bf16 {%0,%1,%2,%3,%4,%5,%6,%7,%8,%9,%10,%11,%12,%13,%14,%15,%16,%17,%18,%19,%20,%21,%22,%23,%24,%25,%26,%27,%28,%29,%30,%31,%32,%33,%34,%35,%36,%37,%38,%39,%40,%41,%42,%43,%44,%45,%46,%47,%48,%49,%50,%51,%52,%53,%54,%55,%56,%57,%58,%59,%60,%61,%62,%63}, %64, %65, 1, 1, 1, %66, %67;"
    : "+f"(d[0]), "+f"(d[1]), "+f"(d[2]), "+f"(d[3]), "+f"(d[4]), "+f"(d[5]), "+f"(d[6]), "+f"(d[7]), "+f"(d[8]), "+f"(d[9]), "+f"(d[10]), "+f"(d[11]), "+f"(d[12]), "+f"(d[13]), "+f"(d[14]), "+f"(d[15]), "+f"(d[16]), "+f"(d[17]), "+f"(d[18]), "+f"(d[19]), "+f"(d[20]), "+f"(d[21]), "+f"(d[22]), "+f"(d[23]), "+f"(d[24]), "+f"(d[25]), "+f"(d[26]), "+f"(d[27]), "+f"(d[28]), "+f"(d[29]), "+f"(d[30]), "+f"(d[31]), "+f"(d[32]), "+f"(d[33]), "+f"(d[34]), "+f"(d[35]), "+f"(d[36]), "+f"(d[37]), "+f"(d[38]), "+f"(d[39]), "+f"(d[40]), "+f"(d[41]), "+f"(d[42]), "+f"(d[43]), "+f"(d[44]), "+f"(d[45]), "+f"(d[46]), "+f"(d[47]), "+f"(d[48]), "+f"(d[49]), "+f"(d[50]), "+f"(d[51]), "+f"(d[52]), "+f"(d[53]), "+f"(d[54]), "+f"(d[55]), "+f"(d[56]), "+f"(d[57]), "+f"(d[58]), "+f"(d[59]), "+f"(d[60]), "+f"(d[61]), "+f"(d[62]), "+f"(d[63])
    : "l"(da), "l"(db), "n"(TA), "n"(TB));
}
template <int TA, int TB> DEVI void wg_ss128z(float* d, uint64_t da, uint64_t db) {
  asm volatile("wgmma.mma_async.sync.aligned.m64n128k16.f32.bf16.bf16 {%0,%1,%2,%3,%4,%5,%6,%7,%8,%9,%10,%11,%12,%13,%14,%15,%16,%17,%18,%19,%20,%21,%22,%23,%24,%25,%26,%27,%28,%29,%30,%31,%32,%33,%34,%35,%36,%37,%38,%39,%40,%41,%42,%43,%44,%45,%46,%47,%48,%49,%50,%51,%52,%53,%54,%55,%56,%57,%58,%59,%60,%61,%62,%63}, %64, %65, 0, 1, 1, %66, %67;"
    : "=f"(d[0]), "=f"(d[1]), "=f"(d[2]), "=f"(d[3]), "=f"(d[4]), "=f"(d[5]), "=f"(d[6]), "=f"(d[7]), "=f"(d[8]), "=f"(d[9]), "=f"(d[10]), "=f"(d[11]), "=f"(d[12]), "=f"(d[13]), "=f"(d[14]), "=f"(d[15]), "=f"(d[16]), "=f"(d[17]), "=f"(d[18]), "=f"(d[19]), "=f"(d[20]), "=f"(d[21]), "=f"(d[22]), "=f"(d[23]), "=f"(d[24]), "=f"(d[25]), "=f"(d[26]), "=f"(d[27]), "=f"(d[28]), "=f"(d[29]), "=f"(d[30]), "=f"(d[31]), "=f"(d[32]), "=f"(d[33]), "=f"(d[34]), "=f"(d[35]), "=f"(d[36]), "=f"(d[37]), "=f"(d[38]), "=f"(d[39]), "=f"(d[40]), "=f"(d[41]), "=f"(d[42]), "=f"(d[43]), "=f"(d[44]), "=f"(d[45]), "=f"(d[46]), "=f"(d[47]), "=f"(d[48]), "=f"(d[49]), "=f"(d[50]), "=f"(d[51]), "=f"(d[52]), "=f"(d[53]), "=f"(d[54]), "=f"(d[55]), "=f"(d[56]), "=f"(d[57]), "=f"(d[58]), "=f"(d[59]), "=f"(d[60]), "=f"(d[61]), "=f"(d[62]), "=f"(d[63])
    : "l"(da), "l"(db), "n"(TA), "n"(TB));
}
constexpr int PREP_SMEM = 57344 + 5 * 32768 + 128 + 1024;
__global__ void __launch_bounds__(256, 1) prep_kernel(const __grid_constant__ CUtensorMap mq, const __grid_constant__ CUtensorMap mk,
                                                      const __grid_constant__ CUtensorMap mv, const __grid_constant__ CUtensorMap mo) {
  extern __shared__ __align__(1024) char smem_raw[];
  const uint32_t sb = (smem_u32(smem_raw) + 1023) & ~1023u;
  const int warp = __shfl_sync(0xffffffffu, threadIdx.x >> 5, 0), lane = threadIdx.x & 31;
  const int type = blockIdx.x >> 6, h = (blockIdx.x >> 2) & 15, nq = blockIdx.x & 3, wg = warp >> 2;
  const uint32_t bars = sb + 57344 + 5 * 32768, abuf = sb + 57344;
  asm volatile("griddepcontrol.launch_dependents;");
  if (threadIdx.x == 0) { for (int i = 0; i < 8; i++) mbar_init(bars + i * 8, 1); asm volatile("fence.mbarrier_init.release.cluster;" ::: "memory"); }
  __syncthreads();
  auto load_a = [&](int mt, int slot) {
    e_expect(bars + 8 + mt * 8, 32768);
    if (type == 0) e_tma3d(abuf + slot * 32768, &mq, 0, mt * 64, h * 4, bars + 8 + mt * 8);
    else e_tma2d(abuf + slot * 32768, &mo, mt * 64, h * 256, bars + 8 + mt * 8);
  };
  if (warp == 0) {
    e_expect(bars, 57344);
    e_tma3d(sb, type == 0 ? &mk : &mv, 0, nq * SL, h * 4, bars);
    for (int i = 0; i < 5; i++) load_a(i, i);
  }
  {
    const int gt = blockIdx.x * 256 + threadIdx.x;
    if (gt < 2048) ((uint4*)g_acc)[gt] = make_uint4(0, 0, 0, 0);
    else if (gt < 2048 + NSEG * NH * 4 + NSEG) g_flag[gt - 2048] = 0;
  }
  const float sc = type == 0 ? 0.0625f * 1.4426950408889634f : 1.0f;
  mbar_wait(bars, 0);
  const uint64_t db = mkdesc(sb, 16, 1024, 1);
  for (int mt = wg; mt < 7; mt += 2) {
    const int slot = mt < 5 ? mt : 6 - mt;
    float d[56];
    mbar_wait(bars + 8 + mt * 8, 0);
    const uint64_t da = mkdesc(abuf + slot * 32768, 16, 1024, 1);
    wg_fence();
    if (type == 0) {
      #pragma unroll
      for (int k = 0; k < 16; k++) {
        if (k == 0) wg_ss112z<0, 0>(d, da, db); else wg_ss112<0, 0>(d, da + (k >> 2) * 512 + (k & 3) * 2, db + (k >> 2) * 896 + (k & 3) * 2);
      }
    } else {
      #pragma unroll
      for (int k = 0; k < 16; k++) {
        if (k == 0) wg_ss112z<1, 0>(d, da, db); else wg_ss112<1, 0>(d, da + k * 128, db + (k >> 2) * 896 + (k & 3) * 2);
      }
    }
    wg_commit();
    wg_wait<0>();
    acc_fence<56>(d);
    if (mt < 2) { bar_sync_id(1 + wg, 128); if ((warp & 3) == 0) load_a(6 - mt, mt); }
    uint4* dst = g_frag[type] + ((size_t)(h * 28 + mt * 4 + (warp & 3)) * 28 + 7 * nq) * 32 + lane;
    #pragma unroll
    for (int k = 0; k < 7; k++)
      dst[k * 32] = make_uint4(pack_bf(d[8 * k] * sc, d[8 * k + 1] * sc), pack_bf(d[8 * k + 2] * sc, d[8 * k + 3] * sc),
                               pack_bf(d[8 * k + 4] * sc, d[8 * k + 5] * sc), pack_bf(d[8 * k + 6] * sc, d[8 * k + 7] * sc));
  }
}
#define NOVA 3
#define KRF 20
#define RPE 0
#define FDEP 4
#define NPH 3
#define C2AT 0
#define RDELAY 500
constexpr int KOV = 28 - KRF;
constexpr int XS_OFF = 0, XS_SZ = 28672;
constexpr int BOV_OFF = XS_OFF + 2 * XS_SZ;
constexpr int YT_OFF = BOV_OFF + KOV * 2048, YT_SZ = 7168;
constexpr int VT_OFF = YT_OFF + 2 * YT_SZ, VT_SZ = 8960;
constexpr int ONES_OFF = VT_OFF + 2 * VT_SZ;
constexpr int MEM_OFF = ONES_OFF + 128, MEM_P = 912;
constexpr int RP_OFF = MEM_OFF + 8 * MEM_P;
constexpr int AOV_OFF = RP_OFF + 8 * 1792;
constexpr int ZER_OFF = AOV_OFF + 4 * NOVA * 512;
constexpr int DUMP_OFF = ZER_OFF + 128;
constexpr int RXX_OFF = DUMP_OFF + 256;
constexpr int LOC_OFF = RXX_OFF + 1024;
constexpr int R_END = LOC_OFF + 2048;
constexpr int BAR_OFF = 204800;
constexpr int TIM_OFF = BAR_OFF + 256;
constexpr int MAIN_SMEM = TIM_OFF + 2048 + 1024;
static_assert(R_END <= BAR_OFF, "smem");
enum { B_MEM1 = 1, B_MEM2, B_C2, B_W, B_RED, B_LOC, B_LOX };
constexpr uint32_t CNT = 0x41800000u;
constexpr unsigned VFLAG_N = 64 * 5;
#define TIM(i)
#define GT(c, i)
DEVI void delay_until(unsigned tend) { long long c; do { c = clock64(); } while ((int)((unsigned)c - tend) < 0); }

DEVI void r_score(const bf16* mem0, uint32_t sb, int h, int j, int warp, int lane_) {
  const int q = warp;
  uint32_t aw[49 - NOVA][4];
  int lane = lane_;
  constexpr int UA[7] = {0, 3, 6, 9, 2, 8, 5}, UB[7] = {1, 4, 7, 10, 12, 13, 11};
  #pragma unroll
  for (int i = 0; i < 49; i++) {
    const uint2* base = (const uint2*)(g_frag[0] + ((size_t)(h * 28 + 7 * j + i % 7) * 28 + 7 * q) * 32 + lane);
    uint2 lo = base[(UA[i / 7] >> 1) * 64 + (UA[i / 7] & 1)], hi = base[(UB[i / 7] >> 1) * 64 + (UB[i / 7] & 1)];
    if (i < 49 - NOVA) { aw[i < 49 - NOVA ? i : 0][0] = lo.x; aw[i < 49 - NOVA ? i : 0][1] = lo.y; aw[i < 49 - NOVA ? i : 0][2] = hi.x; aw[i < 49 - NOVA ? i : 0][3] = hi.y; }
    else sts128(sb + AOV_OFF + (q * NOVA + i - (49 - NOVA)) * 512 + lane * 16, make_uint4(lo.x, lo.y, hi.x, hi.y));
  }
  uint4 w[4];
  {
    uint32_t t[14];
    #pragma unroll
    for (int u = 0; u < 14; u++) t[u] = *(const uint32_t*)(mem0 + (lane >> 2) * D + SL * q + 8 * u + 2 * (lane & 3));
    #pragma unroll
    for (int i = 0; i < 4; i++) { w[i].x = t[3 * i]; w[i].y = t[3 * i + 1]; w[i].z = t[3 * i + 2]; w[i].w = ((t[12 + (i >> 1)] >> ((i & 1) * 16)) & 0xffffu) | CNT; }
  }
  const uint32_t d2m = sb + BAR_OFF + 16;
  unsigned* const vflag = g_flag + NSEG * NH * 4;
  const uint32_t a_m = sb + MEM_OFF + (lane & 7) * MEM_P + (lane >> 3) * 16;
  const char* rp = g_acc;
  for (int s = 0; s < NSEG; s++) {
    const uint32_t a_st = a_m + 224 * q, l3 = lane >= 24;
    uint32_t a_s0 = a_st + l3 * 144, a_s1 = a_st + 48 + l3 * 80, a_s2 = a_st + 96 + l3 * 64;
    asm volatile("" : "+r"(a_s0), "+r"(a_s1), "+r"(a_s2));
    if (__builtin_expect(__any_sync(0xffffffffu, (w[0].w & w[1].w & w[2].w & w[3].w & CNT) != CNT), 0)) {
      int spin = 0;
      do {
        #pragma unroll
        for (int i = 0; i < 4; i++) w[i] = ldg128_relaxed(rp + i * 1024);
        if (++spin > SPIN_LIMIT) __trap();
      } while (__any_sync(0xffffffffu, (w[0].w & w[1].w & w[2].w & w[3].w & CNT) != CNT));
    }
    TIM(0);
    uint32_t mb[14];
    mb[0] = w[0].x; mb[1] = w[0].y; mb[2] = w[1].x; mb[3] = w[1].y; mb[4] = w[2].x; mb[5] = w[2].y; mb[6] = w[3].x; mb[7] = w[3].y;
    mb[8] = w[0].z; mb[9] = __byte_perm(w[0].w, w[1].w, 0x5410); mb[10] = w[2].z; mb[11] = __byte_perm(w[2].w, w[3].w, 0x5410); mb[12] = w[1].z; mb[13] = w[3].z;
    float acc[7][4], se[4], so[4];
    uint32_t pk[14], qa[14], zr;
    {
      stsm4(a_s0, mb[0], mb[1], mb[8], mb[9]); stsm4(a_s1, mb[2], mb[3], mb[12], mb[13]);
      stsm4(a_s2, mb[4], mb[5], mb[10], mb[11]); stsm2(a_st + 144, mb[6], mb[7]);
      bar_arrive<B_MEM1, 256>();
      zr = lds32(sb + ZER_OFF);
    }
    OPAQUE(lane);
    #pragma unroll
    for (int i = 0; i < 49; i++) {
      const int m = i % 7, ks = i / 7, f = i < 49 - NOVA ? i : 0;
      if (i == 48) {
        bar_sync<B_MEM2, 128>();
        const uint32_t a = a_m + 224 * j;
        ldsm4(a, qa[0], qa[1], qa[2], qa[3]); ldsm4(a + 64, qa[4], qa[5], qa[6], qa[7]); ldsm4(a + 128, qa[8], qa[9], qa[10], qa[11]); ldsm2(a + 192, qa[12], qa[13]);
      }
      if (m == 0 && ks >= 1 && ks < 6 && ((FDEP >> ks) & 1)) {
        uint32_t t = 0;
        #pragma unroll
        for (int e = 0; e < 7; e++) t |= __float_as_uint(acc[e][0]);
        mb[2 * (ks + 1)] |= t & zr;
      }
      if (i >= 49 - NOVA) { uint4 v = lds128(sb + AOV_OFF + (q * NOVA + i - (49 - NOVA)) * 512 + lane * 16); mma16816(acc[m], v.x, v.y, v.z, v.w, mb[2 * ks], mb[2 * ks + 1]); }
      else if (ks == 0) mma16816z(acc[m], aw[f][0], aw[f][1], aw[f][2], aw[f][3], mb[0], mb[1]);
      else mma16816(acc[m], aw[f][0], aw[f][1], aw[f][2], aw[f][3], mb[2 * ks], mb[2 * ks + 1]);
    }
    const uint32_t a_rp = sb + RP_OFF + ((s & 1) * 4 + q) * 1792 + lane * 16;
    {
      float te[4], to[4];
      #pragma unroll
      for (int mm = 0; mm < 6; mm += 2) {
        pk[2 * mm] = pack_bf(acc[mm][0], acc[mm][1]); pk[2 * mm + 1] = pack_bf(acc[mm][2], acc[mm][3]);
        pk[2 * mm + 2] = pack_bf(acc[mm + 1][0], acc[mm + 1][1]); pk[2 * mm + 3] = pack_bf(acc[mm + 1][2], acc[mm + 1][3]);
        uint32_t b0 = movm(pk[2 * mm]), b1 = movm(pk[2 * mm + 2]), b2 = movm(pk[2 * mm + 1]), b3 = movm(pk[2 * mm + 3]);
        const uint32_t* qq = qa + 2 * mm;
        if (mm == 0) { mma16816z(se, qq[0], qq[1], qq[2], qq[3], b0, b1); mma16816z(so, qq[0], qq[1], qq[2], qq[3], b2, b3); }
        else if (mm == 2) { mma16816z(te, qq[0], qq[1], qq[2], qq[3], b0, b1); mma16816z(to, qq[0], qq[1], qq[2], qq[3], b2, b3); }
        else { mma16816(se, qq[0], qq[1], qq[2], qq[3], b0, b1); mma16816(so, qq[0], qq[1], qq[2], qq[3], b2, b3); }
        if (mm <= RPE) stsm4(a_rp + mm * 256, pk[2 * mm], pk[2 * mm + 1], pk[2 * mm + 2], pk[2 * mm + 3]);
        if (mm == C2AT) bar_arrive<B_C2, 256>();
      }
      pk[12] = pack_bf(acc[6][0], acc[6][1]); pk[13] = pack_bf(acc[6][2], acc[6][3]);
      mma1688(te, qa[12], qa[13], movm(pk[12])); mma1688(to, qa[12], qa[13], movm(pk[13]));
      sts64f(sb + LOC_OFF + q * 512 + lane * 16, (se[0] + so[2]) + (te[0] + to[2]), (se[1] + so[3]) + (te[1] + to[3]));
      if (C2AT == 6) bar_arrive<B_C2, 256>();
    }
    TIM(1);
    const uint32_t rr = (j + q) & 3;
    const uint32_t l_addr = sb + RXX_OFF + j * 128 + lane * 4;
    uint32_t r_addr = mapa(l_addr, rr), r_bar = mapa(d2m, rr), a_loc = sb + LOC_OFF + lane * 16;
    asm volatile("" : "+r"(r_addr), "+r"(r_bar), "+r"(a_loc));
    bar_sync<B_LOC, 256>();
    {
      uint4 p0 = lds128(a_loc), p1 = lds128(a_loc + 512), p2 = lds128(a_loc + 1024), p3 = lds128(a_loc + 1536);
#define SUM4(c) ((__uint_as_float(p0.c) + __uint_as_float(p1.c)) + (__uint_as_float(p2.c) + __uint_as_float(p3.c)))
      const uint32_t vm = pack_bf(SUM4(x), SUM4(y)), vx = pack_bf(SUM4(z), SUM4(w));
      asm volatile("{.reg .pred p, e;\nsetp.ne.s32 p, %0, 0;\n"
        "@p st.async.weak.shared::cluster.mbarrier::complete_tx::bytes.u32 [%1+512], %3, [%2];\n"
        "@p st.async.weak.shared::cluster.mbarrier::complete_tx::bytes.u32 [%1], %4, [%2];\n"
        "@!p st.shared.u32 [%1+512], %3;\n@!p st.shared.u32 [%1], %4;\n"
        "bar.warp.sync 0xffffffff;\nelect.sync _|e, 0xffffffff;\nand.pred e, e, !p;\n"
        "@e mbarrier.arrive.expect_tx.shared::cta.b64 _, [%2], 768;\n}" :: "r"(q), "r"(r_addr), "r"(r_bar), "r"(vm), "r"(vx) : "memory");
    }
    #pragma unroll
    for (int mm = 0; mm < 6; mm += 2) if (mm > RPE) stsm4(a_rp + mm * 256, pk[2 * mm], pk[2 * mm + 1], pk[2 * mm + 2], pk[2 * mm + 3]);
    stsm2(a_rp + 1536, pk[12], pk[13]);
    TIM(2);
    const uint32_t vb = sb + VT_OFF + (s & 1) * VT_SZ;
    const int r8 = lane & 7, i4 = lane >> 3;
    const uint32_t c3 = 8 * (12 + (q >> 1)) + r8 + (q & 1);
    const uint32_t ones = sb + ONES_OFF + ((q & 1) ? 0 : 16);
    uint32_t zf[4][4];
    #pragma unroll
    for (int i = 0; i < 3; i++) ldsm4(vb + (1 + i4) * 1792 + (8 * (3 * q + i) + r8) * 16, zf[i][0], zf[i][1], zf[i][2], zf[i][3]);
    ldsm4((r8 & 1) ? ones : vb + (1 + i4) * 1792 + c3 * 16, zf[3][0], zf[3][1], zf[3][2], zf[3][3]);
    const uint32_t goff = i4 * 256 + r8 * 16;
    const char* slot = g_acc + (((s + 1) >> 1) * 16384 + ((s + 1) & 1) * 128);
    const char* accw = slot + (j * 4 + q) * 1024 + goff;
    uint32_t a_w = i4 < 3 ? vb + (8 * (3 * q + i4) + r8) * 16 : ((r8 & 1) ? ones : vb + c3 * 16);
    uint32_t a_rx = sb + RXX_OFF + lane * 16;
    asm volatile("" : "+r"(a_w), "+r"(a_rx), "+l"(accw));
    TIM(3);
    mbar_wait(d2m, s & 1);
    TIM(4);
    uint32_t x0, x1, x2, x3, v0, v1, v2, v3;
    ldsm4(a_rx + 512, v0, v1, v2, v3);
    ldsm4(a_rx, x0, x1, x2, x3);
    const float s0 = (bf_lo(v0) + bf_lo(v1)) + (bf_lo(v2) + bf_lo(v3)), s1 = (bf_hi(v0) + bf_hi(v1)) + (bf_hi(v2) + bf_hi(v3));
    uint32_t xm; asm("{.reg .b32 a, b; max.bf16x2 a, %1, %2; max.bf16x2 b, %3, %4; max.bf16x2 %0, a, b;}" : "=r"(xm) : "r"(x0), "r"(x1), "r"(x2), "r"(x3));
    float mx = fmaxf(fmaxf(bf_lo(xm), bf_hi(xm)), fmaxf(s0, s1));
    { float m1 = __shfl_xor_sync(0xffffffffu, mx, 1), m2 = __shfl_xor_sync(0xffffffffu, mx, 2), m3 = __shfl_xor_sync(0xffffffffu, mx, 3);
      mx = fmaxf(fmaxf(mx, m1), fmaxf(m2, m3)); }
    bar_sync<B_W, 256>();
    uint32_t wf[4];
    ldsm4(a_w, wf[0], wf[1], wf[2], wf[3]);
    const uint32_t p1 = pack_bf(ex2(bf_lo(x0) - mx), ex2(bf_hi(x0) - mx)), p2 = pack_bf(ex2(bf_lo(x1) - mx), ex2(bf_hi(x1) - mx));
    const uint32_t p3 = pack_bf(ex2(bf_lo(x2) - mx), ex2(bf_hi(x2) - mx)), p4 = pack_bf(ex2(bf_lo(x3) - mx), ex2(bf_hi(x3) - mx));
    const uint32_t p0 = pack_bf(ex2(s0 - mx), ex2(s1 - mx));
    TIM(5);
    float o[4][4];
    #pragma unroll
    for (int i = 3; i >= 0; i--) mma16816z(o[i], p1, p1, p2, p2, zf[i][0], zf[i][1]);
    #pragma unroll
    for (int i = 3; i >= 0; i--) mma16816(o[i], p3, p3, p4, p4, zf[i][2], zf[i][3]);
    #pragma unroll
    for (int i = 3; i >= 0; i--) mma1688(o[i], p0, p0, wf[i]);
    const float inv = rcpf(o[3][1]);
    sts32(sb + DUMP_OFF, __float_as_uint(o[0][2]));
    bar_arrive<B_RED, 256>();
    uint32_t w0 = pack_bf(o[0][0] * inv, o[0][1] * inv), w1 = pack_bf(o[1][0] * inv, o[1][1] * inv), w2 = pack_bf(o[2][0] * inv, o[2][1] * inv), w3 = pack_bf(o[3][0] * inv, 1.0f);
    asm volatile("red.relaxed.gpu.global.add.noftz.v4.bf16x2 [%0], {%1,%2,%3,%4};" :: "l"(accw), "r"(w0), "r"(w1), "r"(w2), "r"(w3) : "memory");
    unsigned t0 = clk32();
    fence_async_smem();
    __syncwarp();
    bulk_wait<0>();
    if (s > 0) e_red_add(vflag + s - 1, 1);
    e_s2g_commit(g_kt + ((size_t)((s * NH + h) * 8 + q) * D + SL * j) * 8, sb + RP_OFF + ((s & 1) * 4 + q) * 1792, 1792);
    if (s == NSEG - 1) { bulk_wait<0>(); e_red_add(vflag + s, 1); break; }
    TIM(6);
    GT(h == 1 && j == 1 && q == 0 && (s & 7) == 0, 8 + (s >> 3));
    rp = slot + q * 4096 + goff;
    asm volatile("" : "+l"(rp));
    delay_until(t0 + RDELAY);
    TIM(7);
    #pragma unroll
    for (int i = 0; i < 4; i++) w[i] = ldg128_relaxed(rp + i * 1024);
  }
}

DEVI void r_value(const CUtensorMap* xmap, uint32_t sb, int h, int j, int warp, int lane) {
  const int v = warp - 4;
  uint32_t b0[28][4], b1[KRF][4];
  const uint32_t bov = sb + BOV_OFF;
  #pragma unroll
  for (int ks = 27; ks >= 0; ks--) {
    uint4 x = make_uint4(0, 0, 0, 0);
    if (v < 3) x = g_frag[1][((size_t)(h * 28 + 7 * j + 4 + v) * 28 + ks) * 32 + lane];
    if (ks < KRF) { b1[ks < KRF ? ks : 0][0] = x.x; b1[ks < KRF ? ks : 0][1] = x.y; b1[ks < KRF ? ks : 0][2] = x.z; b1[ks < KRF ? ks : 0][3] = x.w; }
    else stsm4(bov + (ks - KRF) * 2048 + (lane >> 4) * 1024 + v * 256 + (lane & 15) * 16, x.x, x.y, x.z, x.w);
  }
  #pragma unroll
  for (int ks = 0; ks < 28; ks++) {
    uint4 x = g_frag[1][((size_t)(h * 28 + 7 * j + v) * 28 + ks) * 32 + lane];
    b0[ks][0] = x.x; b0[ks][1] = x.y; b0[ks][2] = x.z; b0[ks][3] = x.w;
  }
  fence_async_smem();
  bar_sync<B_LOX, 128>();
  const uint32_t xfull = sb + BAR_OFF, d2m = sb + BAR_OFF + 16;
  unsigned* const vflag = g_flag + NSEG * NH * 4;
  const unsigned* const yflag = g_flag + h * 4 + j;
  unsigned yf = 0;
  auto loads = [&](int s) {
    if (v == 1) { e_expect(xfull + (s & 1) * 8, XS_SZ + YT_SZ); e_tma3d_mc(sb + XS_OFF + (s & 1) * XS_SZ + j * 7168, xmap, 0, s * SEG + 8 * j, 0, xfull + (s & 1) * 8, 15); }
    else if (v == 2) {
      if (__builtin_expect(__any_sync(0xffffffffu, yf < 7), 0)) wait_flag(yflag + s * 64, 7);
      fence_async_global();
      e_g2s(sb + YT_OFF + (s & 1) * YT_SZ, g_kt + (size_t)((s * NH + h) * 8 + 4 + j) * D * 8, YT_SZ, xfull + (s & 1) * 8);
      yf = ldg_relaxed(yflag + (s + 1) * 64);
    }
  };
  auto exports = [&](int s) {
    e_s2g_commit(g_vt + (size_t)((s * NH + h) * 4 + j) * 5 * SL * 8, sb + VT_OFF + (s & 1) * VT_SZ, VT_SZ);
  };
  loads(0); loads(1);
  uint32_t yb[14];
  mbar_wait(xfull, 0);
  for (int s = -1; s < NSEG; s++) {
    if (s >= 0) {
      OPAQUE(lane);
      const uint32_t a_m = sb + MEM_OFF + (lane & 7) * MEM_P + (lane >> 3) * 16;
      bar_sync<B_MEM1, 256>();
      TIM(0);
      {
        uint32_t qa[3][4], qb0, qb1; float se[4], so[4], te[4], to[4];
        const uint32_t aj = a_m + 224 * v;
        ldsm4(aj, qa[0][0], qa[0][1], qa[0][2], qa[0][3]); ldsm4(aj + 64, qa[1][0], qa[1][1], qa[1][2], qa[1][3]);
        ldsm4(aj + 128, qa[2][0], qa[2][1], qa[2][2], qa[2][3]); ldsm2(aj + 192, qb0, qb1);
        mma16816z(se, qa[0][0], qa[0][1], qa[0][2], qa[0][3], yb[0], yb[1]); mma16816z(so, qa[0][0], qa[0][1], qa[0][2], qa[0][3], yb[2], yb[3]);
        mma16816z(te, qa[1][0], qa[1][1], qa[1][2], qa[1][3], yb[4], yb[5]); mma16816z(to, qa[1][0], qa[1][1], qa[1][2], qa[1][3], yb[6], yb[7]);
        mma16816(se, qa[2][0], qa[2][1], qa[2][2], qa[2][3], yb[8], yb[9]); mma16816(so, qa[2][0], qa[2][1], qa[2][2], qa[2][3], yb[10], yb[11]);
        mma1688(te, qb0, qb1, yb[12]); mma1688(to, qb0, qb1, yb[13]);
        sts64f(sb + LOC_OFF + v * 512 + lane * 16 + 8, ((se[0] + so[2]) + (te[0] + to[2])), ((se[1] + so[3]) + (te[1] + to[3])));
        bar_arrive<B_LOC, 256>();
      }
      TIM(1);
      {
        const uint32_t a_b = bov + (lane >> 4) * 1024 + v * 256 + (lane & 15) * 16;
        constexpr int ord[14] = {13, 12, 11, 0, 1, 2, 10, 3, 4, 5, 6, 7, 8, 9};
        uint32_t b[14][4], a[14][2][4];
        auto ldround = [&](int i) {
          ldsm4(a_m + ord[i] * 64, b[i][0], b[i][1], b[i][2], b[i][3]);
          #pragma unroll
          for (int e = 0; e < 2; e++) if (2 * ord[i] + e >= KRF) ldsm4(a_b + (2 * ord[i] + e - KRF) * 2048, a[i][e][0], a[i][e][1], a[i][e][2], a[i][e][3]);
        };
        #pragma unroll
        for (int i = 0; i < NPH; i++) ldround(i);
        bar_sync<B_C2, 256>();
        { uint32_t z = lds32(sb + ZER_OFF); b[0][0] |= z; b[0][2] |= z; }
        float wa[4][4];
        TIM(2);
        #pragma unroll
        for (int i = 0; i < 14; i++) {
          if (i + NPH < 14) ldround(i + NPH < 14 ? i + NPH : 0);
          #pragma unroll
          for (int e = 0; e < 2; e++) {
            const int kk = 2 * ord[i] + e, kr = kk < KRF ? kk : 0;
            const uint32_t a0 = kk < KRF ? b1[kr][0] : a[i][e][0], a1 = kk < KRF ? b1[kr][1] : a[i][e][1], a2 = kk < KRF ? b1[kr][2] : a[i][e][2], a3 = kk < KRF ? b1[kr][3] : a[i][e][3];
            if (i == 0) { mma16816z(wa[e], b0[kk][0], b0[kk][1], b0[kk][2], b0[kk][3], b[i][2 * e], b[i][2 * e + 1]); mma16816z(wa[2 + e], a0, a1, a2, a3, b[i][2 * e], b[i][2 * e + 1]); }
            else { mma16816(wa[e], b0[kk][0], b0[kk][1], b0[kk][2], b0[kk][3], b[i][2 * e], b[i][2 * e + 1]); mma16816(wa[2 + e], a0, a1, a2, a3, b[i][2 * e], b[i][2 * e + 1]); }
          }
        }
        const uint32_t aw_ = (v == 3 && lane >= 16) ? sb + DUMP_OFF + (lane & 15) * 16 : sb + VT_OFF + (s & 1) * VT_SZ + ((lane >> 4) * 64 + 16 * v + (lane & 15)) * 16;
        stsm4(aw_, pack_bf((wa[0][0] + wa[1][0]), (wa[0][1] + wa[1][1])), pack_bf((wa[0][2] + wa[1][2]), (wa[0][3] + wa[1][3])),
                   pack_bf((wa[2][0] + wa[3][0]), (wa[2][1] + wa[3][1])), pack_bf((wa[2][2] + wa[3][2]), (wa[2][3] + wa[3][3])));
        bar_arrive<B_W, 256>();
        fence_async_smem();
        TIM(3);
      }
      if (v == 0) { bulk_wait<0>(); if (s > 0) e_red_add(vflag + s - 1, 1); }
      else if (v == 3) { bulk_wait<0>(); e_s2g_commit(g_acc + ((s + 4) >> 1) * 16384 + (s & 1) * 128 + (h * 4 + j) * 256, sb + ZER_OFF, 128); }
      else if (s + 2 < NSEG) { if (v == 1) mbar_wait(d2m, s & 1); loads(s + 2); }
      if (s < NSEG - 1) mbar_wait(xfull + ((s + 1) & 1) * 8, ((s + 1) >> 1) & 1);
      bar_sync<B_RED, 256>();
      TIM(4);
    }
    if (s == NSEG - 1) break;
    float z0[16], z1[16];
    {
      const uint32_t xs = sb + XS_OFF + ((s + 1) & 1) * XS_SZ;
      const uint64_t desc = (uint64_t)((xs & 0x3FFFF) >> 4) | (1ull << 16) | ((uint64_t)(7168 >> 4) << 32) | (1ull << 62);
      const uint64_t da = (uint64_t)((bov & 0x3FFFF) >> 4) | ((uint64_t)(1024 >> 4) << 16) | ((uint64_t)(128 >> 4) << 32);
      wg_fence();
      #pragma unroll
      for (int ks = 0; ks < 28; ks++) {
        const uint64_t db = desc + (ks >> 2) * 64 + (ks & 3) * 2;
        if (ks == 0) { wg_rs32z<0>(z0, b0[0], db); wg_rs32z<0>(z1, b1[0], db); }
        else {
          wg_rs32<0>(z0, b0[ks], db);
          if (ks < KRF) wg_rs32<0>(z1, b1[ks < KRF ? ks : 0], db);
        }
      }
      wg_commit();
      #pragma unroll
      for (int ks = KRF; ks < 28; ks++) wg_ss32<0, 0>(z1, da + (ks - KRF) * 128, desc + (ks >> 2) * 64 + (ks & 3) * 2);
      wg_commit();
    }
    if (v == 0 && s >= 0) exports(s);
    OPAQUE(lane);
    const uint32_t az = sb + VT_OFF + ((s + 1) & 1) * VT_SZ + (1 + (lane >> 4)) * 1792 + (16 * v + (lane & 15)) * 16;
    wg_wait<1>();
    #pragma unroll
    for (int i = 0; i < 16; i++) asm volatile("" : "+f"(z0[i]) :: "memory");
    stsm4(az, pack_bf(z0[0], z0[1]), pack_bf(z0[2], z0[3]), pack_bf(z0[4], z0[5]), pack_bf(z0[6], z0[7]));
    stsm4(az + 2 * 1792, pack_bf(z0[8], z0[9]), pack_bf(z0[10], z0[11]), pack_bf(z0[12], z0[13]), pack_bf(z0[14], z0[15]));
    {
      const uint32_t ay = sb + YT_OFF + ((s + 1) & 1) * YT_SZ + v * 1792, ap = ay + ((lane & 7) | ((lane & 8) << 1) | ((lane & 16) >> 1)) * 16;
      ldsm4t(ap, yb[0], yb[1], yb[2], yb[3]); ldsm4t(ap + 512, yb[4], yb[5], yb[6], yb[7]);
      ldsm4t(ap + 1024, yb[8], yb[9], yb[10], yb[11]); ldsm2t(ay + 1536 + lane * 16, yb[12], yb[13]);
    }
    wg_wait<0>();
    #pragma unroll
    for (int i = 0; i < 16; i++) asm volatile("" : "+f"(z1[i]) :: "memory");
    TIM(5);
    if (v < 3) {
      stsm4(az + 1024, pack_bf(z1[0], z1[1]), pack_bf(z1[2], z1[3]), pack_bf(z1[4], z1[5]), pack_bf(z1[6], z1[7]));
      stsm4(az + 1024 + 2 * 1792, pack_bf(z1[8], z1[9]), pack_bf(z1[10], z1[11]), pack_bf(z1[12], z1[13]), pack_bf(z1[14], z1[15]));
    }
    TIM(6);
  }
  if (v == 0) { exports(NSEG - 1); bulk_wait<0>(); e_red_add(vflag + NSEG - 1, 1); }
}

constexpr int HYS_OFF = 4 * XS_SZ;
constexpr int FX_OFF = 98304, FP_OFF = 155648, FO_OFF = 196608, FO_P = 240;

DEVI void h_keys(const CUtensorMap* xmap, uint32_t sb, int hid, int nhelp, int r, int warp, int lane) {
  const int wg = warp >> 2, w = warp & 3;
  const uint32_t xfull = sb + BAR_OFF + 24, xempty = sb + BAR_OFF + 56;
  int it = 0;
  for (int u0 = 0; u0 < 112; u0 += 2 * nhelp) {
    const int uu = u0 + hid * 2 + wg;
    const bool live = uu < 112;
    const int h = live ? uu / 7 : 0, mt = live ? uu % 7 : 0;
    auto load_x = [&](int s, int n) {
      if (n >= 4) mbar_wait(xempty + (n & 3) * 8, ((n >> 2) - 1) & 1);
      e_expect(xfull + (n & 3) * 8, XS_SZ);
      e_tma3d_mc(sb + (n & 3) * XS_SZ + r * 7168, xmap, 0, s * SEG + 8 * r, 0, xfull + (n & 3) * 8, 15);
    };
    if (warp == 1) for (int i = 0; i < 3; i++) load_x(i, it + i);
    uint32_t a[28][4];
    #pragma unroll
    for (int ks = 0; ks < 28; ks++) {
      uint4 x = g_frag[0][((size_t)(h * 28 + mt * 4 + w) * 28 + ks) * 32 + lane];
      a[ks][0] = x.x; a[ks][1] = x.y; a[ks][2] = x.z; a[ks][3] = x.w;
    }
    for (int s = 0; s < NSEG; s++, it++) {
      float z[16];
      mbar_wait(xfull + (it & 3) * 8, (it >> 2) & 1);
      const uint64_t db = mkdesc(sb + (it & 3) * XS_SZ, 16, 7168, 1);
      wg_fence();
      #pragma unroll
      for (int ks = 0; ks < 28; ks++) { if (ks == 0) wg_rs32z<0>(z, a[0], db); else wg_rs32<0>(z, a[ks], db + (ks >> 2) * 64 + (ks & 3) * 2); }
      wg_commit();
      wg_wait<0>();
      acc_fence<16>(z);
      const uint32_t st = sb + HYS_OFF + (wg * 2 + (s & 1)) * 4096, az = st + (lane >> 4) * 1024 + (16 * w + (lane & 15)) * 16;
      stsm4(az, pack_bf(z[0], z[1]), pack_bf(z[2], z[3]), pack_bf(z[4], z[5]), pack_bf(z[6], z[7]));
      stsm4(az + 2048, pack_bf(z[8], z[9]), pack_bf(z[10], z[11]), pack_bf(z[12], z[13]), pack_bf(z[14], z[15]));
      fence_async_smem();
      unsigned* fl = g_flag + (s * NH + h) * 4 + w;
      bulk_wait<0>();
      if (live && s > 2) e_red_add(fl - 64, 1);
      bar_sync_id(1 + wg, 128);
      if (w == 0 && lane < 4) mbar_arrive_remote(mapa(xempty + (it & 3) * 8, lane));
      __syncwarp();
      if (live) {
        e_s2g_commit(g_kt + ((size_t)((s * NH + h) * 8 + 4 + w) * D + 64 * mt) * 8, st + w * 1024, 1024);
        if (s < 2 || s == NSEG - 1) { bulk_wait<0>(); e_red_add(fl, 1); }
      }
      if (warp == 1 && s + 3 < NSEG) load_x(s + 3, it + 3);
    }
  }
}

DEVI void h_finish(const CUtensorMap* xmap, const CUtensorMap* ktmap, bf16* out, uint32_t sb, int cl, int ncl, int r, int warp, int lane) {
  const int wg = warp >> 2, w = warp & 3, g = lane >> 2, t = lane & 3;
  const uint32_t fx = sb + BAR_OFF + 88, kfull = sb + BAR_OFF + 96, vfull = sb + BAR_OFF + 120, pfull = sb + BAR_OFF + 152;
  const unsigned* vflag = g_flag + NSEG * NH * 4;
  int kslot = 0, kph = 0, par = 0;
  for (int s = cl; s < NSEG; s += ncl, par ^= 1) {
    auto load_k = [&](int c, int slot) { e_expect(kfull + slot * 8, 32768); e_tma3d(sb + slot * 32768, ktmap, 0, 2 * c, (s * NH + 4 * r) * 8, kfull + slot * 8); };
    if (warp == 1) {
      e_expect(fx, 2 * XS_SZ);
      e_tma3d_mc(sb + FX_OFF + r * 7168, xmap, 0, s * SEG + 8 * r, 0, fx, 15);
      e_tma3d_mc(sb + FX_OFF + XS_SZ + r * 7168, xmap, 0, s * SEG + 8 * r, 0, fx, 15);
    }
    if (warp == 0) {
      wait_flag(vflag + s, VFLAG_N);
      fence_async_global();
      int sl = kslot;
      for (int c = 0; c < 3; c++) { load_k(c, sl); if (++sl == 3) sl = 0; }
    }
    float d[64];
    mbar_wait(fx, par);
    const uint64_t da = mkdesc(sb + FX_OFF, 16, 7168, 1);
    #pragma unroll
    for (int c = 0; c < 7; c++) {
      mbar_wait(kfull + kslot * 8, kph);
      const uint64_t db = mkdesc(sb + kslot * 32768 + wg * 16384, 128, 1024, 0);
      wg_fence();
      #pragma unroll
      for (int k = 0; k < 4; k++) { if (c == 0 && k == 0) wg_ss128z<0, 1>(d, da, db); else wg_ss128<0, 1>(d, da + c * 64 + k * 2, db + k * 16); }
      wg_commit();
      wg_wait<0>();
      if (c < 4 || c == 6) bar_sync<3, 256>();
      if (warp == 0 && c < 4) load_k(c + 3, kslot);
      if (++kslot == 3) { kslot = 0; kph ^= 1; }
    }
    acc_fence<64>(d);
    if (warp == 0) {
      for (int i = 0; i < 4; i++) e_expect(vfull + i * 8, 4 * VT_SZ);
      for (int i = 0; i < 16; i++) e_g2s(sb + i * VT_SZ, g_vt + (size_t)((s * NH + i) * 4 + r) * 5 * SL * 8, VT_SZ, vfull + (i >> 2) * 8);
    }
    {
      float e[32];
      #pragma unroll
      for (int i = 0; i < 32; i++) e[i] = (w & 2) ? d[32 + i] : d[i];
      uint32_t pp[10];
      #pragma unroll
      for (int hf = 0; hf < 2; hf++) {
        const int row = 16 * (w & 1) + 8 * hf + g;
        float v[10];
        v[0] = (e[2 * hf] + e[4 + 2 * hf]) + (e[8 + 2 * hf] + e[12 + 2 * hf]);
        v[1] = (e[2 * hf + 1] + e[5 + 2 * hf]) + (e[9 + 2 * hf] + e[13 + 2 * hf]);
        float mx = fmaxf(v[0], v[1]);
        #pragma unroll
        for (int i = 0; i < 8; i++) {
          const int key = 8 * (i >> 1) + 2 * t + (i & 1);
          v[2 + i] = key <= row ? e[16 + 4 * (i >> 1) + 2 * hf + (i & 1)] : -INFINITY;
          mx = fmaxf(mx, v[2 + i]);
        }
        mx = fmaxf(mx, __shfl_xor_sync(0xffffffffu, mx, 1));
        mx = fmaxf(mx, __shfl_xor_sync(0xffffffffu, mx, 2));
        float sum = 0;
        #pragma unroll
        for (int i = 0; i < 10; i++) { v[i] = ex2(v[i] - mx); sum += v[i]; }
        sum += __shfl_xor_sync(0xffffffffu, sum, 1);
        sum += __shfl_xor_sync(0xffffffffu, sum, 2);
        const float inv = rcpf(sum);
        #pragma unroll
        for (int i = 0; i < 5; i++) pp[2 * i + hf] = pack_bf(v[2 * i] * inv, v[2 * i + 1] * inv);
      }
      const uint32_t ap = sb + FP_OFF + (4 * r + 2 * wg + (w >> 1)) * 2560 + (lane >> 4) * 512 + (16 * (w & 1) + (lane & 15)) * 16;
      stsm4(ap, pp[0], pp[1], pp[2], pp[3]); stsm4(ap + 1024, pp[4], pp[5], pp[6], pp[7]); stsm2(ap + 2048, pp[8], pp[9]);
    }
    fence_async_smem();
    bar_sync<3, 256>();
    if (warp == 0) e_expect(pfull, 3 * 10240);
    else if (warp < 4) { const uint32_t peer = (r + warp) & 3, src = sb + FP_OFF + r * 10240; e_s2c(mapa(src, peer), src, 10240, mapa(pfull, peer)); }
    mbar_wait(pfull, par);
    float o[16];
    const uint64_t dv = mkdesc(sb + wg * 1024, 1792, 128, 0), dp = mkdesc(sb + FP_OFF, 512, 128, 0);
    #pragma unroll
    for (int i = 0; i < 4; i++) {
      mbar_wait(vfull + i * 8, par);
      wg_fence();
      #pragma unroll
      for (int k = 10 * i; k < 10 * i + 10; k++) { if (k == 0) wg_ss32z<0, 0>(o, dv, dp); else wg_ss32<0, 0>(o, dv + k * 224, dp + k * 64); }
      wg_commit();
    }
    wg_wait<0>();
    acc_fence<16>(o);
    if (warp < 7) {
      const uint32_t ao = sb + FO_OFF + (8 * (lane >> 4) + (lane & 7)) * FO_P + (16 * warp + (lane & 8)) * 2;
      stsm4t(ao, pack_bf(o[0], o[1]), pack_bf(o[2], o[3]), pack_bf(o[4], o[5]), pack_bf(o[6], o[7]));
      stsm4t(ao + 16 * FO_P, pack_bf(o[8], o[9]), pack_bf(o[10], o[11]), pack_bf(o[12], o[13]), pack_bf(o[14], o[15]));
    }
    bar_sync<3, 256>();
    for (int i = warp * 32 + lane; i < 448; i += 256) {
      const int q = i / 14, c = i % 14;
      *(uint4*)(out + (size_t)(s * SEG + q) * OUTW + D + SL * r + c * 8) = lds128(sb + FO_OFF + q * FO_P + c * 16);
    }
    cluster_sync_relaxed();
  }
}

__global__ void __launch_bounds__(256, 1) main_kernel(const __grid_constant__ CUtensorMap xmap, const __grid_constant__ CUtensorMap ktmap,
                                                      const bf16* __restrict__ mem0, bf16* __restrict__ out) {
  extern __shared__ __align__(1024) char smem_raw[];
  const uint32_t sb = (smem_u32(smem_raw) + 1023) & ~1023u;
  const int warp = __shfl_sync(0xffffffffu, threadIdx.x >> 5, 0), lane = threadIdx.x & 31;
  const int cl = blockIdx.x >> 2, r = blockIdx.x & 3;
  asm volatile("griddepcontrol.launch_dependents;");
  GT(blockIdx.x == 5 && threadIdx.x == 0, 2);
  if (threadIdx.x == 0) {
    for (int i = 0; i < 20; i++) mbar_init(sb + BAR_OFF + i * 8, (i >= 7 && i < 11) ? 8 : 1);
    asm volatile("fence.mbarrier_init.release.cluster;" ::: "memory");
  }
  if (cl < NH && threadIdx.x < 32) { sts32(sb + ONES_OFF + threadIdx.x * 4, 0x3f803f80u); sts32(sb + ZER_OFF + threadIdx.x * 4, 0); }
  fence_async_smem();
  __syncthreads();
  cluster_sync_full();
  asm volatile("griddepcontrol.wait;" ::: "memory");
  GT(blockIdx.x == 5 && threadIdx.x == 0, 3);
  if (cl < NH) {
    if (warp < 4) {
      asm volatile("pmevent 2;");
      r_score(mem0, sb, cl, r, warp, lane);
      GT(blockIdx.x == 5 && threadIdx.x == 0, 4);
    } else {
      asm volatile("pmevent 3;");
      r_value(&xmap, sb, cl, r, warp, lane);
    }
    cluster_sync_relaxed();
  } else {
    asm volatile("pmevent 4;");
    const int ncl = (gridDim.x >> 2) - NH;
    h_keys(&xmap, sb, blockIdx.x - 4 * NH, 4 * ncl, r, warp, lane);
    GT(blockIdx.x == 64 && threadIdx.x == 0, 5);
    cluster_sync_relaxed();
    h_finish(&xmap, &ktmap, out, sb, cl - NH, ncl, r, warp, lane);
    GT(r == 0 && threadIdx.x == 0, 32 + cl);
  }
}
constexpr int A_NEW = 50, A_TILES = (SEQ + A_NEW - 1) / A_NEW, A_NS = 3;
constexpr int AX_OFF = 0, AR_OFF = 57344, AO_OFF = AR_OFF + A_NS * 16384, AO_P = 464, AQ_OFF = AO_OFF + 64 * AO_P, AQ_P = 456, AQ_SZ = 64 * AQ_P;
constexpr int AB_OFF = AQ_OFF + 3 * AQ_SZ, A_SMEM = AB_OFF + 128 + 1024;
__global__ void __launch_bounds__(384, 1) parta_kernel(const __grid_constant__ CUtensorMap xmap, const __grid_constant__ CUtensorMap wmap,
                                                       const __grid_constant__ CUtensorMap omap, bf16* __restrict__ out) {
  extern __shared__ __align__(1024) char smem_raw[];
  const uint32_t sb = (smem_u32(smem_raw) + 1023) & ~1023u;
  const int warp = __shfl_sync(0xffffffffu, threadIdx.x >> 5, 0), lane = threadIdx.x & 31;
  const int row0 = blockIdx.x * A_NEW - 14;
  const uint32_t full = sb + AB_OFF, empty = full + 8 * A_NS, xbar = empty + 8 * A_NS;
  GT(threadIdx.x == 0, 80 + blockIdx.x);
  if (threadIdx.x == 0) {
    for (int i = 0; i < A_NS; i++) { mbar_init(full + i * 8, 1); mbar_init(empty + i * 8, 8); }
    mbar_init(xbar, 1);
    asm volatile("fence.mbarrier_init.release.cluster;" ::: "memory");
  }
  __syncthreads();
  if (warp >= 8) {
    asm volatile("setmaxnreg.dec.sync.aligned.u32 24;");
    if (warp == 8) {
      e_expect(xbar, 57344);
      e_tma3d(sb + AX_OFF, &xmap, 0, row0, 0, xbar);
      int slot = 0, ph = 1;
      #pragma unroll 1
      for (int p = 0; p < 8; p++) {
        const int c0 = p < 6 ? (p % 3) * D + (p / 3) * 224 : (p - 6) * 224;
        const CUtensorMap* m = p < 6 ? &wmap : &omap;
        #pragma unroll 1
        for (int k = 0; k < 14; k++) {
          mbar_wait(empty + slot * 8, ph);
          const uint32_t dst = sb + AR_OFF + slot * 16384, bar = full + slot * 8;
          e_expect(bar, 16384);
          e_tma2d(dst, m, c0, k * 32, bar); e_tma2d(dst + 4096, m, c0 + 64, k * 32, bar);
          e_tma2d(dst + 8192, m, c0 + 112, k * 32, bar); e_tma2d(dst + 12288, m, c0 + 176, k * 32, bar);
          if (++slot == A_NS) { slot = 0; ph ^= 1; }
        }
      }
    }
  } else {
    asm volatile("setmaxnreg.inc.sync.aligned.u32 240;");
    const int wg = warp >> 2, w = warp & 3, g = lane >> 2, t = lane & 3;
    int slot = 0, ph = 0;
    auto gemm_pass = [&](const uint32_t (&a)[28][4], float* d) {
      int prev = 0;
      #pragma unroll
      for (int k = 0; k < 14; k++) {
        mbar_wait(full + slot * 8, ph);
        const uint64_t db = mkdesc(sb + AR_OFF + slot * 16384 + wg * 8192, 4096, 1024, 1);
        wg_fence();
        if (k == 0) wg_rs112z<1>(d, a[0], db); else wg_rs112<1>(d, a[2 * k], db);
        wg_rs112<1>(d, a[2 * k + 1], db + 128);
        wg_commit();
        if (k > 0) { wg_wait<1>(); e_arrive(empty + prev * 8); }
        prev = slot;
        if (++slot == A_NS) { slot = 0; ph ^= 1; }
      }
      wg_wait<0>();
      e_arrive(empty + prev * 8);
      acc_fence<56>(d);
    };
    mbar_wait(xbar, 0);
    #pragma unroll 1
    for (int hf = 0; hf < 2; hf++) {
      {
        uint32_t a[28][4];
        const int rr = 16 * w + (lane & 15);
        #pragma unroll
        for (int ks = 0; ks < 28; ks++)
          ldsm4(sb + AX_OFF + (ks >> 2) * 8192 + rr * 128 + ((((ks & 3) * 2 + (lane >> 4)) ^ (rr & 7)) << 4), a[ks][0], a[ks][1], a[ks][2], a[ks][3]);
        #pragma unroll 1
        for (int m = 0; m < 3; m++) {
          float d[56];
          gemm_pass(a, d);
          if (m == 0) bar_sync<1, 256>();
          const uint32_t q = sb + AQ_OFF + m * AQ_SZ + (16 * w + g) * AQ_P + (112 * wg + 2 * t) * 2;
          #pragma unroll
          for (int nb = 0; nb < 14; nb++) { sts32(q + nb * 16, pack_bf(d[4 * nb], d[4 * nb + 1])); sts32(q + 8 * AQ_P + nb * 16, pack_bf(d[4 * nb + 2], d[4 * nb + 3])); }
        }
      }
      bar_sync<1, 256>();
      if (lane < 26) {
        const int ra = 14 + 4 * (lane >> 1) + (lane & 1), rb = min(ra + 2, 63);
        const uint32_t qb = sb + AQ_OFF + warp * 56, kb = qb + AQ_SZ, vb = kb + AQ_SZ;
        float sa[8], sc[8];
        {
          float qa[28], qc[28];
          #pragma unroll
          for (int i = 0; i < 7; i++) {
            uint2 u = lds64(qb + ra * AQ_P + i * 8), v = lds64(qb + rb * AQ_P + i * 8);
            qa[4 * i] = bf_lo(u.x); qa[4 * i + 1] = bf_hi(u.x); qa[4 * i + 2] = bf_lo(u.y); qa[4 * i + 3] = bf_hi(u.y);
            qc[4 * i] = bf_lo(v.x); qc[4 * i + 1] = bf_hi(v.x); qc[4 * i + 2] = bf_lo(v.y); qc[4 * i + 3] = bf_hi(v.y);
          }
          #pragma unroll
          for (int n = 0; n < 9; n++) {
            const uint32_t ka = kb + (n == 0 ? rb : ra + 2 - 2 * n) * AQ_P;
            float x0 = 0, x1 = 0, y0 = 0, y1 = 0;
            #pragma unroll
            for (int i = 0; i < 7; i++) {
              uint2 u = lds64(ka + i * 8);
              const float k0 = bf_lo(u.x), k1 = bf_hi(u.x), k2 = bf_lo(u.y), k3 = bf_hi(u.y);
              if (n > 0) { x0 = fmaf(qa[4 * i], k0, x0); x1 = fmaf(qa[4 * i + 1], k1, x1); x0 = fmaf(qa[4 * i + 2], k2, x0); x1 = fmaf(qa[4 * i + 3], k3, x1); }
              if (n < 8) { y0 = fmaf(qc[4 * i], k0, y0); y1 = fmaf(qc[4 * i + 1], k1, y1); y0 = fmaf(qc[4 * i + 2], k2, y0); y1 = fmaf(qc[4 * i + 3], k3, y1); }
            }
            const bool ok = row0 + ra + 2 - 2 * n >= 0;
            if (n > 0) sa[n > 0 ? n - 1 : 0] = ok ? x0 + x1 : -INFINITY;
            if (n < 8) sc[n < 8 ? n : 0] = ok ? y0 + y1 : -INFINITY;
          }
        }
        const float scl = 0.18898223650461361f * 1.4426950408889634f;
        float ma = sa[0], mc = sc[0], da = 0, dc = 0;
        #pragma unroll
        for (int n = 1; n < 8; n++) { ma = fmaxf(ma, sa[n]); mc = fmaxf(mc, sc[n]); }
        #pragma unroll
        for (int n = 0; n < 8; n++) { sa[n] = ex2((sa[n] - ma) * scl); sc[n] = ex2((sc[n] - mc) * scl); da += sa[n]; dc += sc[n]; }
        da = rcpf(da); dc = rcpf(dc);
        float oa[28], oc[28];
        #pragma unroll
        for (int i = 0; i < 28; i++) { oa[i] = 0; oc[i] = 0; }
        #pragma unroll
        for (int n = 0; n < 9; n++) {
          const uint32_t va = vb + (n == 0 ? rb : ra + 2 - 2 * n) * AQ_P;
          const float pa = sa[n > 0 ? n - 1 : 0], pc = sc[n < 8 ? n : 0];
          #pragma unroll
          for (int i = 0; i < 7; i++) {
            uint2 u = lds64(va + i * 8);
            const float v0 = bf_lo(u.x), v1 = bf_hi(u.x), v2 = bf_lo(u.y), v3 = bf_hi(u.y);
            if (n > 0) { oa[4 * i] = fmaf(pa, v0, oa[4 * i]); oa[4 * i + 1] = fmaf(pa, v1, oa[4 * i + 1]); oa[4 * i + 2] = fmaf(pa, v2, oa[4 * i + 2]); oa[4 * i + 3] = fmaf(pa, v3, oa[4 * i + 3]); }
            if (n < 8) { oc[4 * i] = fmaf(pc, v0, oc[4 * i]); oc[4 * i + 1] = fmaf(pc, v1, oc[4 * i + 1]); oc[4 * i + 2] = fmaf(pc, v2, oc[4 * i + 2]); oc[4 * i + 3] = fmaf(pc, v3, oc[4 * i + 3]); }
          }
        }
        const uint32_t ob = sb + (hf == 0 ? AO_OFF : AX_OFF) + warp * 56;
        #pragma unroll
        for (int i = 0; i < 7; i++) {
          sts64(ob + ra * AO_P + i * 8, pack_bf(oa[4 * i] * da, oa[4 * i + 1] * da), pack_bf(oa[4 * i + 2] * da, oa[4 * i + 3] * da));
          if (ra + 2 < 64) sts64(ob + rb * AO_P + i * 8, pack_bf(oc[4 * i] * dc, oc[4 * i + 1] * dc), pack_bf(oc[4 * i + 2] * dc, oc[4 * i + 3] * dc));
        }
      }
      __syncwarp();
    }
    bar_sync<1, 256>();
    {
      uint32_t a[28][4];
      const uint32_t ro = (16 * w + (lane & 15)) * AO_P + (lane >> 4) * 16;
      #pragma unroll
      for (int ks = 0; ks < 28; ks++) ldsm4(sb + (ks < 14 ? AO_OFF + ks * 32 : AX_OFF + (ks - 14) * 32) + ro, a[ks][0], a[ks][1], a[ks][2], a[ks][3]);
      #pragma unroll 1
      for (int m = 0; m < 2; m++) {
        float d[56];
        gemm_pass(a, d);
        const uint32_t st = sb + AQ_OFF + warp * 3840;
        __syncwarp();
        #pragma unroll
        for (int k = 0; k < 7; k++)
          stsm4(st + (lane & 15) * 240 + (lane >> 4) * 16 + k * 32, pack_bf(d[8 * k], d[8 * k + 1]), pack_bf(d[8 * k + 2], d[8 * k + 3]), pack_bf(d[8 * k + 4], d[8 * k + 5]), pack_bf(d[8 * k + 6], d[8 * k + 7]));
        __syncwarp();
        #pragma unroll
        for (int i = 0; i < 7; i++) {
          const int id = i * 32 + lane, rr = id / 14, c = id % 14, tr = 16 * w + rr;
          const uint4 v = lds128(st + rr * 240 + c * 16);
          if (tr >= 14 && row0 + tr < SEQ) *(uint4*)(out + (size_t)(row0 + tr) * OUTW + m * 224 + wg * 112 + c * 8) = v;
        }
      }
    }
    GT(threadIdx.x == 0, 130 + blockIdx.x);
  }
}
typedef CUresult (*EncodeFn)(CUtensorMap*, CUtensorMapDataType, cuuint32_t, void*, const cuuint64_t*, const cuuint64_t*, const cuuint32_t*, const cuuint32_t*,
                             CUtensorMapInterleave, CUtensorMapSwizzle, CUtensorMapL2promotion, CUtensorMapFloatOOBfill);
static void make_map(EncodeFn enc, CUtensorMap* m, const void* p, int rank, cuuint64_t d0, cuuint64_t d1, cuuint64_t d2, cuuint64_t s1, cuuint64_t s2,
                     cuuint32_t b0, cuuint32_t b1, cuuint32_t b2, bool swz) {
  cuuint64_t gd[3] = {d0, d1, d2}, gs[2] = {s1, s2}; cuuint32_t bx[3] = {b0, b1, b2}, es[3] = {1, 1, 1};
  enc(m, CU_TENSOR_MAP_DATA_TYPE_BFLOAT16, rank, (void*)p, gd, gs, bx, es, CU_TENSOR_MAP_INTERLEAVE_NONE,
      swz ? CU_TENSOR_MAP_SWIZZLE_128B : CU_TENSOR_MAP_SWIZZLE_NONE, CU_TENSOR_MAP_L2_PROMOTION_L2_128B, CU_TENSOR_MAP_FLOAT_OOB_FILL_NONE);
}

extern "C" void kernel_launch(void* const* d_in, const int* in_sizes, int n_in, void* d_out, int out_size) {
  static EncodeFn enc = nullptr;
  static int ncl = 0;
  static void* kt = nullptr;
  cudaLaunchAttribute at[2];
  at[0].id = cudaLaunchAttributeProgrammaticStreamSerialization; at[0].val.programmaticStreamSerializationAllowed = 1;
  at[1].id = cudaLaunchAttributeClusterDimension; at[1].val.clusterDim.x = 4; at[1].val.clusterDim.y = 1; at[1].val.clusterDim.z = 1;
  if (!enc) {
    void* fn = nullptr; cudaDriverEntryPointQueryResult qr;
    cudaGetDriverEntryPoint("cuTensorMapEncodeTiled", &fn, cudaEnableDefault, &qr);
    enc = (EncodeFn)fn;
    cudaFuncSetAttribute(prep_kernel, cudaFuncAttributeMaxDynamicSharedMemorySize, PREP_SMEM);
    cudaFuncSetAttribute(main_kernel, cudaFuncAttributeMaxDynamicSharedMemorySize, MAIN_SMEM);
    cudaFuncSetAttribute(parta_kernel, cudaFuncAttributeMaxDynamicSharedMemorySize, A_SMEM);
    cudaGetSymbolAddress(&kt, g_kt);
    cudaLaunchConfig_t q = {}; q.gridDim = dim3(120); q.blockDim = dim3(256); q.dynamicSmemBytes = MAIN_SMEM; q.attrs = at + 1; q.numAttrs = 1;
    cudaOccupancyMaxActiveClusters(&ncl, main_kernel, &q);
    if (ncl > 30) ncl = 30;
  }
  CUtensorMap ax, aw, ao, bx, mq, mk, mv, mo, mkt;
  make_map(enc, &ax, d_in[0], 3, 64, SEQ, 7, 896, 128, 64, 64, 7, true);
  make_map(enc, &aw, d_in[1], 2, 1344, D, 1, 2688, 0, 64, 32, 1, true);
  make_map(enc, &ao, d_in[2], 2, D, D, 1, 896, 0, 64, 32, 1, true);
  make_map(enc, &bx, d_in[3], 3, 64, SEQ, 7, 896, 128, 64, 8, 7, true);
  make_map(enc, &mq, d_in[5], 3, 64, D, 64, 8192, 128, 64, 64, 4, true);
  make_map(enc, &mk, d_in[6], 3, 64, D, 64, 8192, 128, 64, SL, 4, true);
  make_map(enc, &mv, d_in[7], 3, 64, D, 64, 8192, 128, 64, SL, 4, true);
  make_map(enc, &mo, d_in[8], 2, D, 4096, 1, 896, 0, 64, 256, 1, true);
  make_map(enc, &mkt, kt, 3, 256, 14, NSEG * NH * 8, 512, 7168, 256, 2, 32, false);
  cudaLaunchConfig_t c = {};
  c.stream = cudaStreamPerThread;
  c.gridDim = dim3(128); c.blockDim = dim3(256); c.dynamicSmemBytes = PREP_SMEM; c.attrs = at; c.numAttrs = 0;
  cudaLaunchKernelEx(&c, prep_kernel, mq, mk, mv, mo);
  c.gridDim = dim3(ncl * 4); c.dynamicSmemBytes = MAIN_SMEM; c.numAttrs = 2;
  cudaLaunchKernelEx(&c, main_kernel, bx, mkt, (const bf16*)d_in[4], (bf16*)d_out);
  c.gridDim = dim3(A_TILES); c.blockDim = dim3(384); c.dynamicSmemBytes = A_SMEM; c.numAttrs = 1;
  cudaLaunchKernelEx(&c, parta_kernel, ax, aw, ao, (bf16*)d_out);
}
```

```cpp
#include <cuda_runtime.h>
#include <cuda_bf16.h>
#include <cuda.h>
#include <stdint.h>
#include <type_traits>
#define DEVI __device__ __forceinline__
typedef __nv_bfloat16 bf16;

DEVI uint32_t smem_u32(const void* p) { return (uint32_t)__cvta_generic_to_shared(p); }
DEVI uint32_t mapa(uint32_t a, uint32_t r) { uint32_t o; asm("mapa.shared::cluster.u32 %0, %1, %2;" : "=r"(o) : "r"(a), "r"(r)); return o; }
DEVI unsigned clk32() { unsigned c; asm volatile("mov.u32 %0, %%clock;" : "=r"(c) :: "memory"); return c; }
DEVI void mbar_init(uint32_t bar, uint32_t n) { asm volatile("mbarrier.init.shared::cta.b64 [%0], %1;" :: "r"(bar), "r"(n) : "memory"); }
DEVI void mbar_arrive(uint32_t bar) { asm volatile("mbarrier.arrive.shared::cta.b64 _, [%0];" :: "r"(bar) : "memory"); }
DEVI void mbar_arrive_remote(uint32_t bar) { asm volatile("mbarrier.arrive.relaxed.cluster.shared::cluster.b64 _, [%0];" :: "r"(bar) : "memory"); }
#define SPIN_LIMIT 2000000
DEVI void mbar_wait(uint32_t bar, uint32_t par) {
  asm volatile("{\n.reg .pred p;\n.reg .u32 c;\nmbarrier.try_wait.parity.shared::cta.b64 p, [%0], %1;\n@p bra LD;\nmov.u32 c, 0;\nLW:\n"
               "mbarrier.try_wait.parity.shared::cta.b64 p, [%0], %1;\n@p bra LD;\nadd.u32 c, c, 1;\nsetp.lt.u32 p, c, 400000;\n@p bra LW;\ntrap;\nLD:\n}" :: "r"(bar), "r"(par) : "memory");
}
template <int ID, int N> DEVI void bar_sync() { asm volatile("bar.sync %0, %1;" :: "n"(ID), "n"(N) : "memory"); }
template <int ID, int N> DEVI void bar_arrive() { asm volatile("bar.arrive %0, %1;" :: "n"(ID), "n"(N) : "memory"); }
DEVI void bar_sync_id(int id, int n) { asm volatile("bar.sync %0, %1;" :: "r"(id), "r"(n) : "memory"); }
DEVI void fence_async_smem() { asm volatile("fence.proxy.async.shared::cta;" ::: "memory"); }
DEVI void fence_async_global() { asm volatile("fence.proxy.async.global;" ::: "memory"); }
DEVI void mma16816(float* c, uint32_t a0, uint32_t a1, uint32_t a2, uint32_t a3, uint32_t b0, uint32_t b1) {
  asm volatile("mma.sync.aligned.m16n8k16.row.col.f32.bf16.bf16.f32 {%0,%1,%2,%3}, {%4,%5,%6,%7}, {%8,%9}, {%0,%1,%2,%3};"
    : "+f"(c[0]), "+f"(c[1]), "+f"(c[2]), "+f"(c[3]) : "r"(a0), "r"(a1), "r"(a2), "r"(a3), "r"(b0), "r"(b1));
}
DEVI void mma16816z(float* c, uint32_t a0, uint32_t a1, uint32_t a2, uint32_t a3, uint32_t b0, uint32_t b1) {
  asm volatile("mma.sync.aligned.m16n8k16.row.col.f32.bf16.bf16.f32 {%0,%1,%2,%3}, {%4,%5,%6,%7}, {%8,%9}, {%10,%10,%10,%10};"
    : "=f"(c[0]), "=f"(c[1]), "=f"(c[2]), "=f"(c[3]) : "r"(a0), "r"(a1), "r"(a2), "r"(a3), "r"(b0), "r"(b1), "f"(0.f));
}
DEVI void mma1688(float* c, uint32_t a0, uint32_t a1, uint32_t b0) {
  asm volatile("mma.sync.aligned.m16n8k8.row.col.f32.bf16.bf16.f32 {%0,%1,%2,%3}, {%4,%5}, {%6}, {%0,%1,%2,%3};"
    : "+f"(c[0]), "+f"(c[1]), "+f"(c[2]), "+f"(c[3]) : "r"(a0), "r"(a1), "r"(b0));
}
DEVI void ldsm4(uint32_t a, uint32_t& r0, uint32_t& r1, uint32_t& r2, uint32_t& r3) { asm volatile("ldmatrix.sync.aligned.m8n8.x4.shared.b16 {%0,%1,%2,%3}, [%4];" : "=r"(r0), "=r"(r1), "=r"(r2), "=r"(r3) : "r"(a) : "memory"); }
DEVI void ldsm2(uint32_t a, uint32_t& r0, uint32_t& r1) { asm volatile("ldmatrix.sync.aligned.m8n8.x2.shared.b16 {%0,%1}, [%2];" : "=r"(r0), "=r"(r1) : "r"(a) : "memory"); }
DEVI void ldsm4t(uint32_t a, uint32_t& r0, uint32_t& r1, uint32_t& r2, uint32_t& r3) { asm volatile("ldmatrix.sync.aligned.m8n8.x4.trans.shared.b16 {%0,%1,%2,%3}, [%4];" : "=r"(r0), "=r"(r1), "=r"(r2), "=r"(r3) : "r"(a) : "memory"); }
DEVI void ldsm2t(uint32_t a, uint32_t& r0, uint32_t& r1) { asm volatile("ldmatrix.sync.aligned.m8n8.x2.trans.shared.b16 {%0,%1}, [%2];" : "=r"(r0), "=r"(r1) : "r"(a) : "memory"); }
DEVI void stsm4(uint32_t a, uint32_t r0, uint32_t r1, uint32_t r2, uint32_t r3) { asm volatile("stmatrix.sync.aligned.m8n8.x4.shared.b16 [%0], {%1,%2,%3,%4};" :: "r"(a), "r"(r0), "r"(r1), "r"(r2), "r"(r3) : "memory"); }
DEVI void stsm2(uint32_t a, uint32_t r0, uint32_t r1) { asm volatile("stmatrix.sync.aligned.m8n8.x2.shared.b16 [%0], {%1,%2};" :: "r"(a), "r"(r0), "r"(r1) : "memory"); }
DEVI void stsm4t(uint32_t a, uint32_t r0, uint32_t r1, uint32_t r2, uint32_t r3) { asm volatile("stmatrix.sync.aligned.m8n8.x4.trans.shared.b16 [%0], {%1,%2,%3,%4};" :: "r"(a), "r"(r0), "r"(r1), "r"(r2), "r"(r3) : "memory"); }
DEVI uint32_t movm(uint32_t a) { uint32_t d; asm volatile("movmatrix.sync.aligned.m8n8.trans.b16 %0, %1;" : "=r"(d) : "r"(a)); return d; }
DEVI uint32_t pack_bf(float lo, float hi) { uint32_t d; asm("cvt.rn.bf16x2.f32 %0, %1, %2;" : "=r"(d) : "f"(hi), "f"(lo)); return d; }
DEVI float bf_lo(uint32_t v) { return __uint_as_float(v << 16); }
DEVI float bf_hi(uint32_t v) { return __uint_as_float(v & 0xffff0000u); }
DEVI float ex2(float x) { float y; asm("ex2.approx.ftz.f32 %0, %1;" : "=f"(y) : "f"(x)); return y; }
DEVI float rcpf(float x) { float y; asm("rcp.approx.ftz.f32 %0, %1;" : "=f"(y) : "f"(x)); return y; }
DEVI uint4 lds128(uint32_t a) { uint4 v; asm volatile("ld.shared.v4.u32 {%0,%1,%2,%3}, [%4];" : "=r"(v.x), "=r"(v.y), "=r"(v.z), "=r"(v.w) : "r"(a) : "memory"); return v; }
DEVI uint2 lds64(uint32_t a) { uint2 v; asm volatile("ld.shared.v2.u32 {%0,%1}, [%2];" : "=r"(v.x), "=r"(v.y) : "r"(a) : "memory"); return v; }
DEVI uint32_t lds32(uint32_t a) { uint32_t v; asm volatile("ld.shared.u32 %0, [%1];" : "=r"(v) : "r"(a) : "memory"); return v; }
DEVI void sts32(uint32_t a, uint32_t v) { asm volatile("st.shared.u32 [%0], %1;" :: "r"(a), "r"(v) : "memory"); }
DEVI void sts64(uint32_t a, uint32_t x, uint32_t y) { asm volatile("st.shared.v2.u32 [%0], {%1,%2};" :: "r"(a), "r"(x), "r"(y) : "memory"); }
DEVI void sts64f(uint32_t a, float x, float y) { asm volatile("st.shared.v2.f32 [%0], {%1,%2};" :: "r"(a), "f"(x), "f"(y) : "memory"); }
DEVI void sts128(uint32_t a, uint4 v) { asm volatile("st.shared.v4.u32 [%0], {%1,%2,%3,%4};" :: "r"(a), "r"(v.x), "r"(v.y), "r"(v.z), "r"(v.w) : "memory"); }
DEVI uint4 ldg128_relaxed(const void* p) { uint4 v; asm volatile("{.reg .b128 t; ld.relaxed.gpu.global.b128 t, [%2]; mov.b128 {%0,%1}, t;}" : "=l"(*(unsigned long long*)&v.x), "=l"(*(unsigned long long*)&v.z) : "l"(p) : "memory"); return v; }
DEVI unsigned ldg_relaxed(const unsigned* p) { unsigned v; asm volatile("ld.relaxed.gpu.global.u32 %0, [%1];" : "=r"(v) : "l"(p) : "memory"); return v; }
template <int NS = 200> DEVI void wait_flag(const unsigned* p, unsigned target) { int spin = 0; while (__any_sync(0xffffffffu, ldg_relaxed(p) < target)) { if (NS) __nanosleep(NS); if (++spin > SPIN_LIMIT) __trap(); } }
template <int N> DEVI void bulk_wait() { asm volatile("cp.async.bulk.wait_group %0;" :: "n"(N) : "memory"); }
#define ELECT "{.reg .pred pe; elect.sync _|pe, 0xffffffff;\n"
DEVI void e_expect(uint32_t bar, uint32_t tx) { asm volatile(ELECT "@pe mbarrier.arrive.expect_tx.shared::cta.b64 _, [%0], %1;}" :: "r"(bar), "r"(tx) : "memory"); }
DEVI void e_arrive(uint32_t bar) { asm volatile(ELECT "@pe mbarrier.arrive.shared::cta.b64 _, [%0];}" :: "r"(bar) : "memory"); }
DEVI void e_g2s(uint32_t dst, const void* src, uint32_t bytes, uint32_t bar) { asm volatile(ELECT "@pe cp.async.bulk.shared::cluster.global.mbarrier::complete_tx::bytes [%0], [%1], %2, [%3];}" :: "r"(dst), "l"(src), "r"(bytes), "r"(bar) : "memory"); }
DEVI void e_s2c(uint32_t dst, uint32_t src, uint32_t bytes, uint32_t bar) { asm volatile(ELECT "@pe cp.async.bulk.shared::cluster.shared::cta.mbarrier::complete_tx::bytes [%0], [%1], %2, [%3];}" :: "r"(dst), "r"(src), "r"(bytes), "r"(bar) : "memory"); }
DEVI void e_s2g(void* dst, uint32_t src, uint32_t bytes) { asm volatile(ELECT "@pe cp.async.bulk.global.shared::cta.bulk_group [%0], [%1], %2;}" :: "l"(dst), "r"(src), "r"(bytes) : "memory"); }
DEVI void bulk_commit() { asm volatile("cp.async.bulk.commit_group;" ::: "memory"); }
DEVI void e_tma3d_mc(uint32_t dst, const CUtensorMap* m, int c0, int c1, int c2, uint32_t bar, uint16_t mask) {
  asm volatile(ELECT "@pe cp.async.bulk.tensor.3d.shared::cluster.global.mbarrier::complete_tx::bytes.multicast::cluster [%0], [%1, {%2,%3,%4}], [%5], %6;}" :: "r"(dst), "l"(m), "r"(c0), "r"(c1), "r"(c2), "r"(bar), "h"(mask) : "memory");
}
DEVI void e_tma3d(uint32_t dst, const CUtensorMap* m, int c0, int c1, int c2, uint32_t bar) {
  asm volatile(ELECT "@pe cp.async.bulk.tensor.3d.shared::cluster.global.mbarrier::complete_tx::bytes [%0], [%1, {%2,%3,%4}], [%5];}" :: "r"(dst), "l"(m), "r"(c0), "r"(c1), "r"(c2), "r"(bar) : "memory");
}
DEVI void e_tma2d(uint32_t dst, const CUtensorMap* m, int c0, int c1, uint32_t bar) {
  asm volatile(ELECT "@pe cp.async.bulk.tensor.2d.shared::cluster.global.mbarrier::complete_tx::bytes [%0], [%1, {%2,%3}], [%4];}" :: "r"(dst), "l"(m), "r"(c0), "r"(c1), "r"(bar) : "memory");
}
DEVI void red_add_if(bool c, unsigned* p, unsigned v) { asm volatile("{.reg .pred p; setp.ne.s32 p, %2, 0; @p red.relaxed.gpu.global.add.u32 [%0], %1;}" :: "l"(p), "r"(v), "r"((int)c) : "memory"); }
DEVI void wg_fence() { asm volatile("wgmma.fence.sync.aligned;" ::: "memory"); }
DEVI void wg_commit() { asm volatile("wgmma.commit_group.sync.aligned;" ::: "memory"); }
template <int N> DEVI void wg_wait() { asm volatile("wgmma.wait_group.sync.aligned %0;" :: "n"(N) : "memory"); }
template <int N> DEVI void acc_fence(float* d) {
  #pragma unroll
  for (int i = 0; i < N; i++) asm volatile("" : "+f"(d[i]) :: "memory");
}
DEVI void cluster_sync_full() { asm volatile("barrier.cluster.arrive.aligned; barrier.cluster.wait.aligned;" ::: "memory"); }
DEVI void cluster_sync_relaxed() { asm volatile("barrier.cluster.arrive.relaxed.aligned; barrier.cluster.wait.aligned;" ::: "memory"); }
DEVI uint64_t mkdesc(uint32_t addr, uint32_t lbo, uint32_t sbo, uint32_t swz) {
  return (uint64_t)((addr & 0x3FFFF) >> 4) | ((uint64_t)(lbo >> 4) << 16) | ((uint64_t)(sbo >> 4) << 32) | ((uint64_t)swz << 62);
}
#define OPAQUE(x) asm volatile("" : "+r"(x))

constexpr int D = 448, NH = 16, SL = 112, SEG = 32, NSEG = 64, SEQ = 2048, OUTW = 896;
__device__ uint4 g_frag[2][NH * 28 * 28 * 32];
constexpr int PL = D * 8;
__device__ __align__(1024) bf16 g_yt[(size_t)NSEG * 64 * PL];
__device__ __align__(1024) bf16 g_vt[(size_t)NSEG * 80 * PL];
__device__ __align__(1024) bf16 g_p[(size_t)NSEG * 80 * 256];
__device__ __align__(1024) char g_accraw[2 * 262144];
__device__ __align__(8) int g_side[160];
DEVI char* acc_base() { return (char*)(((uintptr_t)g_accraw + 262143) & ~(uintptr_t)262143); }
DEVI uint32_t acc_off(int s, int q, int side) {
  const int pair = ((s >> 1) & 3) * 4 + q;
  return (pair * 2 + ((side ^ pair ^ (pair >> 3)) & 1)) * 4096 + (s & 1) * 128;
}
DEVI unsigned* tflag_ptr(int side) { return (unsigned*)(acc_base() + (32 + side) * 4096); }
DEVI unsigned* vflag_ptr(int side) { return (unsigned*)(acc_base() + (36 + side) * 4096); }
#define SAMESIDE 1
DEVI int tpc_side(int sm) { const int2 d = *(const int2*)(g_side + (sm & ~1)); return d.x + d.y > 0; }
DEVI int rec_side() { return SAMESIDE ? __shfl_sync(0xffffffffu, tpc_side(0) ^ 1, 0) : 0; }
DEVI void delay_until(unsigned tend) { long long c; do { c = clock64(); } while ((int)((unsigned)c - tend) < 0); }
#define GT(c, i)
template <int TB> DEVI void wg_rs32(float* d, const uint32_t* a, uint64_t db) {
  asm volatile("wgmma.mma_async.sync.aligned.m64n32k16.f32.bf16.bf16 {%0,%1,%2,%3,%4,%5,%6,%7,%8,%9,%10,%11,%12,%13,%14,%15}, {%16,%17,%18,%19}, %20, 1, 1, 1, %21;"
    : "+f"(d[0]), "+f"(d[1]), "+f"(d[2]), "+f"(d[3]), "+f"(d[4]), "+f"(d[5]), "+f"(d[6]), "+f"(d[7]), "+f"(d[8]), "+f"(d[9]), "+f"(d[10]), "+f"(d[11]), "+f"(d[12]), "+f"(d[13]), "+f"(d[14]), "+f"(d[15])
    : "r"(a[0]), "r"(a[1]), "r"(a[2]), "r"(a[3]), "l"(db), "n"(TB));
}
template <int TB> DEVI void wg_rs32z(float* d, const uint32_t* a, uint64_t db) {
  asm volatile("wgmma.mma_async.sync.aligned.m64n32k16.f32.bf16.bf16 {%0,%1,%2,%3,%4,%5,%6,%7,%8,%9,%10,%11,%12,%13,%14,%15}, {%16,%17,%18,%19}, %20, 0, 1, 1, %21;"
    : "=f"(d[0]), "=f"(d[1]), "=f"(d[2]), "=f"(d[3]), "=f"(d[4]), "=f"(d[5]), "=f"(d[6]), "=f"(d[7]), "=f"(d[8]), "=f"(d[9]), "=f"(d[10]), "=f"(d[11]), "=f"(d[12]), "=f"(d[13]), "=f"(d[14]), "=f"(d[15])
    : "r"(a[0]), "r"(a[1]), "r"(a[2]), "r"(a[3]), "l"(db), "n"(TB));
}
template <int TA, int TB> DEVI void wg_ss32(float* d, uint64_t da, uint64_t db) {
  asm volatile("wgmma.mma_async.sync.aligned.m64n32k16.f32.bf16.bf16 {%0,%1,%2,%3,%4,%5,%6,%7,%8,%9,%10,%11,%12,%13,%14,%15}, %16, %17, 1, 1, 1, %18, %19;"
    : "+f"(d[0]), "+f"(d[1]), "+f"(d[2]), "+f"(d[3]), "+f"(d[4]), "+f"(d[5]), "+f"(d[6]), "+f"(d[7]), "+f"(d[8]), "+f"(d[9]), "+f"(d[10]), "+f"(d[11]), "+f"(d[12]), "+f"(d[13]), "+f"(d[14]), "+f"(d[15])
    : "l"(da), "l"(db), "n"(TA), "n"(TB));
}
template <int TA, int TB> DEVI void wg_ss32z(float* d, uint64_t da, uint64_t db) {
  asm volatile("wgmma.mma_async.sync.aligned.m64n32k16.f32.bf16.bf16 {%0,%1,%2,%3,%4,%5,%6,%7,%8,%9,%10,%11,%12,%13,%14,%15}, %16, %17, 0, 1, 1, %18, %19;"
    : "=f"(d[0]), "=f"(d[1]), "=f"(d[2]), "=f"(d[3]), "=f"(d[4]), "=f"(d[5]), "=f"(d[6]), "=f"(d[7]), "=f"(d[8]), "=f"(d[9]), "=f"(d[10]), "=f"(d[11]), "=f"(d[12]), "=f"(d[13]), "=f"(d[14]), "=f"(d[15])
    : "l"(da), "l"(db), "n"(TA), "n"(TB));
}
template <int TA, int TB> DEVI void wg_ss112(float* d, uint64_t da, uint64_t db) {
  asm volatile("wgmma.mma_async.sync.aligned.m64n112k16.f32.bf16.bf16 {%0,%1,%2,%3,%4,%5,%6,%7,%8,%9,%10,%11,%12,%13,%14,%15,%16,%17,%18,%19,%20,%21,%22,%23,%24,%25,%26,%27,%28,%29,%30,%31,%32,%33,%34,%35,%36,%37,%38,%39,%40,%41,%42,%43,%44,%45,%46,%47,%48,%49,%50,%51,%52,%53,%54,%55}, %56, %57, 1, 1, 1, %58, %59;"
    : "+f"(d[0]), "+f"(d[1]), "+f"(d[2]), "+f"(d[3]), "+f"(d[4]), "+f"(d[5]), "+f"(d[6]), "+f"(d[7]), "+f"(d[8]), "+f"(d[9]), "+f"(d[10]), "+f"(d[11]), "+f"(d[12]), "+f"(d[13]), "+f"(d[14]), "+f"(d[15]), "+f"(d[16]), "+f"(d[17]), "+f"(d[18]), "+f"(d[19]), "+f"(d[20]), "+f"(d[21]), "+f"(d[22]), "+f"(d[23]), "+f"(d[24]), "+f"(d[25]), "+f"(d[26]), "+f"(d[27]), "+f"(d[28]), "+f"(d[29]), "+f"(d[30]), "+f"(d[31]), "+f"(d[32]), "+f"(d[33]), "+f"(d[34]), "+f"(d[35]), "+f"(d[36]), "+f"(d[37]), "+f"(d[38]), "+f"(d[39]), "+f"(d[40]), "+f"(d[41]), "+f"(d[42]), "+f"(d[43]), "+f"(d[44]), "+f"(d[45]), "+f"(d[46]), "+f"(d[47]), "+f"(d[48]), "+f"(d[49]), "+f"(d[50]), "+f"(d[51]), "+f"(d[52]), "+f"(d[53]), "+f"(d[54]), "+f"(d[55])
    : "l"(da), "l"(db), "n"(TA), "n"(TB));
}
template <int TA, int TB> DEVI void wg_ss112z(float* d, uint64_t da, uint64_t db) {
  asm volatile("wgmma.mma_async.sync.aligned.m64n112k16.f32.bf16.bf16 {%0,%1,%2,%3,%4,%5,%6,%7,%8,%9,%10,%11,%12,%13,%14,%15,%16,%17,%18,%19,%20,%21,%22,%23,%24,%25,%26,%27,%28,%29,%30,%31,%32,%33,%34,%35,%36,%37,%38,%39,%40,%41,%42,%43,%44,%45,%46,%47,%48,%49,%50,%51,%52,%53,%54,%55}, %56, %57, 0, 1, 1, %58, %59;"
    : "=f"(d[0]), "=f"(d[1]), "=f"(d[2]), "=f"(d[3]), "=f"(d[4]), "=f"(d[5]), "=f"(d[6]), "=f"(d[7]), "=f"(d[8]), "=f"(d[9]), "=f"(d[10]), "=f"(d[11]), "=f"(d[12]), "=f"(d[13]), "=f"(d[14]), "=f"(d[15]), "=f"(d[16]), "=f"(d[17]), "=f"(d[18]), "=f"(d[19]), "=f"(d[20]), "=f"(d[21]), "=f"(d[22]), "=f"(d[23]), "=f"(d[24]), "=f"(d[25]), "=f"(d[26]), "=f"(d[27]), "=f"(d[28]), "=f"(d[29]), "=f"(d[30]), "=f"(d[31]), "=f"(d[32]), "=f"(d[33]), "=f"(d[34]), "=f"(d[35]), "=f"(d[36]), "=f"(d[37]), "=f"(d[38]), "=f"(d[39]), "=f"(d[40]), "=f"(d[41]), "=f"(d[42]), "=f"(d[43]), "=f"(d[44]), "=f"(d[45]), "=f"(d[46]), "=f"(d[47]), "=f"(d[48]), "=f"(d[49]), "=f"(d[50]), "=f"(d[51]), "=f"(d[52]), "=f"(d[53]), "=f"(d[54]), "=f"(d[55])
    : "l"(da), "l"(db), "n"(TA), "n"(TB));
}
template <int TA, int TB> DEVI void wg_ss64(float* d, uint64_t da, uint64_t db) {
  asm volatile("wgmma.mma_async.sync.aligned.m64n64k16.f32.bf16.bf16 {%0,%1,%2,%3,%4,%5,%6,%7,%8,%9,%10,%11,%12,%13,%14,%15,%16,%17,%18,%19,%20,%21,%22,%23,%24,%25,%26,%27,%28,%29,%30,%31}, %32, %33, 1, 1, 1, %34, %35;"
    : "+f"(d[0]), "+f"(d[1]), "+f"(d[2]), "+f"(d[3]), "+f"(d[4]), "+f"(d[5]), "+f"(d[6]), "+f"(d[7]), "+f"(d[8]), "+f"(d[9]), "+f"(d[10]), "+f"(d[11]), "+f"(d[12]), "+f"(d[13]), "+f"(d[14]), "+f"(d[15]), "+f"(d[16]), "+f"(d[17]), "+f"(d[18]), "+f"(d[19]), "+f"(d[20]), "+f"(d[21]), "+f"(d[22]), "+f"(d[23]), "+f"(d[24]), "+f"(d[25]), "+f"(d[26]), "+f"(d[27]), "+f"(d[28]), "+f"(d[29]), "+f"(d[30]), "+f"(d[31])
    : "l"(da), "l"(db), "n"(TA), "n"(TB));
}
template <int TA, int TB> DEVI void wg_ss64z(float* d, uint64_t da, uint64_t db) {
  asm volatile("wgmma.mma_async.sync.aligned.m64n64k16.f32.bf16.bf16 {%0,%1,%2,%3,%4,%5,%6,%7,%8,%9,%10,%11,%12,%13,%14,%15,%16,%17,%18,%19,%20,%21,%22,%23,%24,%25,%26,%27,%28,%29,%30,%31}, %32, %33, 0, 1, 1, %34, %35;"
    : "=f"(d[0]), "=f"(d[1]), "=f"(d[2]), "=f"(d[3]), "=f"(d[4]), "=f"(d[5]), "=f"(d[6]), "=f"(d[7]), "=f"(d[8]), "=f"(d[9]), "=f"(d[10]), "=f"(d[11]), "=f"(d[12]), "=f"(d[13]), "=f"(d[14]), "=f"(d[15]), "=f"(d[16]), "=f"(d[17]), "=f"(d[18]), "=f"(d[19]), "=f"(d[20]), "=f"(d[21]), "=f"(d[22]), "=f"(d[23]), "=f"(d[24]), "=f"(d[25]), "=f"(d[26]), "=f"(d[27]), "=f"(d[28]), "=f"(d[29]), "=f"(d[30]), "=f"(d[31])
    : "l"(da), "l"(db), "n"(TA), "n"(TB));
}
template <int TB> DEVI void wg_rs192(float* d, const uint32_t* a, uint64_t db) {
  asm volatile("wgmma.mma_async.sync.aligned.m64n192k16.f32.bf16.bf16 {%0,%1,%2,%3,%4,%5,%6,%7,%8,%9,%10,%11,%12,%13,%14,%15,%16,%17,%18,%19,%20,%21,%22,%23,%24,%25,%26,%27,%28,%29,%30,%31,%32,%33,%34,%35,%36,%37,%38,%39,%40,%41,%42,%43,%44,%45,%46,%47,%48,%49,%50,%51,%52,%53,%54,%55,%56,%57,%58,%59,%60,%61,%62,%63,%64,%65,%66,%67,%68,%69,%70,%71,%72,%73,%74,%75,%76,%77,%78,%79,%80,%81,%82,%83,%84,%85,%86,%87,%88,%89,%90,%91,%92,%93,%94,%95}, {%96,%97,%98,%99}, %100, 1, 1, 1, %101;"
    : "+f"(d[0]), "+f"(d[1]), "+f"(d[2]), "+f"(d[3]), "+f"(d[4]), "+f"(d[5]), "+f"(d[6]), "+f"(d[7]), "+f"(d[8]), "+f"(d[9]), "+f"(d[10]), "+f"(d[11]), "+f"(d[12]), "+f"(d[13]), "+f"(d[14]), "+f"(d[15]), "+f"(d[16]), "+f"(d[17]), "+f"(d[18]), "+f"(d[19]), "+f"(d[20]), "+f"(d[21]), "+f"(d[22]), "+f"(d[23]), "+f"(d[24]), "+f"(d[25]), "+f"(d[26]), "+f"(d[27]), "+f"(d[28]), "+f"(d[29]), "+f"(d[30]), "+f"(d[31]), "+f"(d[32]), "+f"(d[33]), "+f"(d[34]), "+f"(d[35]), "+f"(d[36]), "+f"(d[37]), "+f"(d[38]), "+f"(d[39]), "+f"(d[40]), "+f"(d[41]), "+f"(d[42]), "+f"(d[43]), "+f"(d[44]), "+f"(d[45]), "+f"(d[46]), "+f"(d[47]), "+f"(d[48]), "+f"(d[49]), "+f"(d[50]), "+f"(d[51]), "+f"(d[52]), "+f"(d[53]), "+f"(d[54]), "+f"(d[55]), "+f"(d[56]), "+f"(d[57]), "+f"(d[58]), "+f"(d[59]), "+f"(d[60]), "+f"(d[61]), "+f"(d[62]), "+f"(d[63]), "+f"(d[64]), "+f"(d[65]), "+f"(d[66]), "+f"(d[67]), "+f"(d[68]), "+f"(d[69]), "+f"(d[70]), "+f"(d[71]), "+f"(d[72]), "+f"(d[73]), "+f"(d[74]), "+f"(d[75]), "+f"(d[76]), "+f"(d[77]), "+f"(d[78]), "+f"(d[79]), "+f"(d[80]), "+f"(d[81]), "+f"(d[82]), "+f"(d[83]), "+f"(d[84]), "+f"(d[85]), "+f"(d[86]), "+f"(d[87]), "+f"(d[88]), "+f"(d[89]), "+f"(d[90]), "+f"(d[91]), "+f"(d[92]), "+f"(d[93]), "+f"(d[94]), "+f"(d[95])
    : "r"(a[0]), "r"(a[1]), "r"(a[2]), "r"(a[3]), "l"(db), "n"(TB));
}
template <int TB> DEVI void wg_rs192z(float* d, const uint32_t* a, uint64_t db) {
  asm volatile("wgmma.mma_async.sync.aligned.m64n192k16.f32.bf16.bf16 {%0,%1,%2,%3,%4,%5,%6,%7,%8,%9,%10,%11,%12,%13,%14,%15,%16,%17,%18,%19,%20,%21,%22,%23,%24,%25,%26,%27,%28,%29,%30,%31,%32,%33,%34,%35,%36,%37,%38,%39,%40,%41,%42,%43,%44,%45,%46,%47,%48,%49,%50,%51,%52,%53,%54,%55,%56,%57,%58,%59,%60,%61,%62,%63,%64,%65,%66,%67,%68,%69,%70,%71,%72,%73,%74,%75,%76,%77,%78,%79,%80,%81,%82,%83,%84,%85,%86,%87,%88,%89,%90,%91,%92,%93,%94,%95}, {%96,%97,%98,%99}, %100, 0, 1, 1, %101;"
    : "=f"(d[0]), "=f"(d[1]), "=f"(d[2]), "=f"(d[3]), "=f"(d[4]), "=f"(d[5]), "=f"(d[6]), "=f"(d[7]), "=f"(d[8]), "=f"(d[9]), "=f"(d[10]), "=f"(d[11]), "=f"(d[12]), "=f"(d[13]), "=f"(d[14]), "=f"(d[15]), "=f"(d[16]), "=f"(d[17]), "=f"(d[18]), "=f"(d[19]), "=f"(d[20]), "=f"(d[21]), "=f"(d[22]), "=f"(d[23]), "=f"(d[24]), "=f"(d[25]), "=f"(d[26]), "=f"(d[27]), "=f"(d[28]), "=f"(d[29]), "=f"(d[30]), "=f"(d[31]), "=f"(d[32]), "=f"(d[33]), "=f"(d[34]), "=f"(d[35]), "=f"(d[36]), "=f"(d[37]), "=f"(d[38]), "=f"(d[39]), "=f"(d[40]), "=f"(d[41]), "=f"(d[42]), "=f"(d[43]), "=f"(d[44]), "=f"(d[45]), "=f"(d[46]), "=f"(d[47]), "=f"(d[48]), "=f"(d[49]), "=f"(d[50]), "=f"(d[51]), "=f"(d[52]), "=f"(d[53]), "=f"(d[54]), "=f"(d[55]), "=f"(d[56]), "=f"(d[57]), "=f"(d[58]), "=f"(d[59]), "=f"(d[60]), "=f"(d[61]), "=f"(d[62]), "=f"(d[63]), "=f"(d[64]), "=f"(d[65]), "=f"(d[66]), "=f"(d[67]), "=f"(d[68]), "=f"(d[69]), "=f"(d[70]), "=f"(d[71]), "=f"(d[72]), "=f"(d[73]), "=f"(d[74]), "=f"(d[75]), "=f"(d[76]), "=f"(d[77]), "=f"(d[78]), "=f"(d[79]), "=f"(d[80]), "=f"(d[81]), "=f"(d[82]), "=f"(d[83]), "=f"(d[84]), "=f"(d[85]), "=f"(d[86]), "=f"(d[87]), "=f"(d[88]), "=f"(d[89]), "=f"(d[90]), "=f"(d[91]), "=f"(d[92]), "=f"(d[93]), "=f"(d[94]), "=f"(d[95])
    : "r"(a[0]), "r"(a[1]), "r"(a[2]), "r"(a[3]), "l"(db), "n"(TB));
}
template <int TB> DEVI void wg_rs128(float* d, const uint32_t* a, uint64_t db) {
  asm volatile("wgmma.mma_async.sync.aligned.m64n128k16.f32.bf16.bf16 {%0,%1,%2,%3,%4,%5,%6,%7,%8,%9,%10,%11,%12,%13,%14,%15,%16,%17,%18,%19,%20,%21,%22,%23,%24,%25,%26,%27,%28,%29,%30,%31,%32,%33,%34,%35,%36,%37,%38,%39,%40,%41,%42,%43,%44,%45,%46,%47,%48,%49,%50,%51,%52,%53,%54,%55,%56,%57,%58,%59,%60,%61,%62,%63}, {%64,%65,%66,%67}, %68, 1, 1, 1, %69;"
    : "+f"(d[0]), "+f"(d[1]), "+f"(d[2]), "+f"(d[3]), "+f"(d[4]), "+f"(d[5]), "+f"(d[6]), "+f"(d[7]), "+f"(d[8]), "+f"(d[9]), "+f"(d[10]), "+f"(d[11]), "+f"(d[12]), "+f"(d[13]), "+f"(d[14]), "+f"(d[15]), "+f"(d[16]), "+f"(d[17]), "+f"(d[18]), "+f"(d[19]), "+f"(d[20]), "+f"(d[21]), "+f"(d[22]), "+f"(d[23]), "+f"(d[24]), "+f"(d[25]), "+f"(d[26]), "+f"(d[27]), "+f"(d[28]), "+f"(d[29]), "+f"(d[30]), "+f"(d[31]), "+f"(d[32]), "+f"(d[33]), "+f"(d[34]), "+f"(d[35]), "+f"(d[36]), "+f"(d[37]), "+f"(d[38]), "+f"(d[39]), "+f"(d[40]), "+f"(d[41]), "+f"(d[42]), "+f"(d[43]), "+f"(d[44]), "+f"(d[45]), "+f"(d[46]), "+f"(d[47]), "+f"(d[48]), "+f"(d[49]), "+f"(d[50]), "+f"(d[51]), "+f"(d[52]), "+f"(d[53]), "+f"(d[54]), "+f"(d[55]), "+f"(d[56]), "+f"(d[57]), "+f"(d[58]), "+f"(d[59]), "+f"(d[60]), "+f"(d[61]), "+f"(d[62]), "+f"(d[63])
    : "r"(a[0]), "r"(a[1]), "r"(a[2]), "r"(a[3]), "l"(db), "n"(TB));
}
template <int TB> DEVI void wg_rs128z(float* d, const uint32_t* a, uint64_t db) {
  asm volatile("wgmma.mma_async.sync.aligned.m64n128k16.f32.bf16.bf16 {%0,%1,%2,%3,%4,%5,%6,%7,%8,%9,%10,%11,%12,%13,%14,%15,%16,%17,%18,%19,%20,%21,%22,%23,%24,%25,%26,%27,%28,%29,%30,%31,%32,%33,%34,%35,%36,%37,%38,%39,%40,%41,%42,%43,%44,%45,%46,%47,%48,%49,%50,%51,%52,%53,%54,%55,%56,%57,%58,%59,%60,%61,%62,%63}, {%64,%65,%66,%67}, %68, 0, 1, 1, %69;"
    : "=f"(d[0]), "=f"(d[1]), "=f"(d[2]), "=f"(d[3]), "=f"(d[4]), "=f"(d[5]), "=f"(d[6]), "=f"(d[7]), "=f"(d[8]), "=f"(d[9]), "=f"(d[10]), "=f"(d[11]), "=f"(d[12]), "=f"(d[13]), "=f"(d[14]), "=f"(d[15]), "=f"(d[16]), "=f"(d[17]), "=f"(d[18]), "=f"(d[19]), "=f"(d[20]), "=f"(d[21]), "=f"(d[22]), "=f"(d[23]), "=f"(d[24]), "=f"(d[25]), "=f"(d[26]), "=f"(d[27]), "=f"(d[28]), "=f"(d[29]), "=f"(d[30]), "=f"(d[31]), "=f"(d[32]), "=f"(d[33]), "=f"(d[34]), "=f"(d[35]), "=f"(d[36]), "=f"(d[37]), "=f"(d[38]), "=f"(d[39]), "=f"(d[40]), "=f"(d[41]), "=f"(d[42]), "=f"(d[43]), "=f"(d[44]), "=f"(d[45]), "=f"(d[46]), "=f"(d[47]), "=f"(d[48]), "=f"(d[49]), "=f"(d[50]), "=f"(d[51]), "=f"(d[52]), "=f"(d[53]), "=f"(d[54]), "=f"(d[55]), "=f"(d[56]), "=f"(d[57]), "=f"(d[58]), "=f"(d[59]), "=f"(d[60]), "=f"(d[61]), "=f"(d[62]), "=f"(d[63])
    : "r"(a[0]), "r"(a[1]), "r"(a[2]), "r"(a[3]), "l"(db), "n"(TB));
}
#define ROT 0
#define NPROBE 8
#define PHOLD 0
constexpr int PREP_SMEM = 57344 + 5 * 32768 + 128 + 1024;
__global__ void __launch_bounds__(320, 1) prep_kernel(const __grid_constant__ CUtensorMap mq, const __grid_constant__ CUtensorMap mk,
                                                      const __grid_constant__ CUtensorMap mv, const __grid_constant__ CUtensorMap mo) {
  extern __shared__ __align__(1024) char smem_raw[];
  const uint32_t sb = (smem_u32(smem_raw) + 1023) & ~1023u;
  const int warp = __shfl_sync(0xffffffffu, threadIdx.x >> 5, 0), lane = threadIdx.x & 31;
  const int type = blockIdx.x >> 6, h = (blockIdx.x >> 2) & 15, nq = blockIdx.x & 3, wg = warp >> 2;
  const uint32_t bars = sb + 57344 + 5 * 32768, abuf = sb + 57344;
  asm volatile("griddepcontrol.launch_dependents;");
  GT(blockIdx.x == 0 && threadIdx.x == 0, 1);
  if (threadIdx.x == 0) { for (int i = 0; i < 8; i++) mbar_init(bars + i * 8, 1); asm volatile("fence.mbarrier_init.release.cluster;" ::: "memory"); }
  if (warp >= 8) {
    uint32_t smid; asm volatile("mov.u32 %0, %%smid;" : "=r"(smid));
    unsigned* pa = (unsigned*)(acc_base() + 196608 + (warp - 8) * 4096 + (smid & 127) * 32);
    if (lane < 8) pa[lane] = 0;
    unsigned best = 0xffffffffu;
    if (lane == 0) {
      unsigned v = 0;
      #pragma unroll 1
      for (int i = 0; i < NPROBE; i++) {
        const unsigned t0 = clk32();
        v = atomicExch(pa + v, 0);
        unsigned t1 = 0;
        asm volatile("{.reg .pred p; setp.eq.u32 p, %1, 0; @p mov.u32 %0, %%clock;}" : "+r"(t1) : "r"(v) : "memory");
        best = min(best, t1 - t0);
      }
      if (warp == 9) sts32(bars + 64, best);
    }
    __syncwarp();
    if (PHOLD) bar_arrive<4, 320>();
    bar_sync<3, 64>();
    if (warp == 8 && lane == 0 && smid < 156) g_side[smid] = min(max((int)(best - lds32(bars + 64)), -250), 250);
    GT(blockIdx.x == 0 && threadIdx.x == 256, 6);
    return;
  }
  bar_sync<4, PHOLD ? 320 : 256>();
  if (blockIdx.x >= 128) return;
  auto load_a = [&](int mt, int slot) {
    const int row = ((mt + ROT * nq) % 7) * 64;
    e_expect(bars + 8 + mt * 8, 32768);
    if (type == 0) e_tma3d(abuf + slot * 32768, &mq, 0, row, h * 4, bars + 8 + mt * 8);
    else e_tma2d(abuf + slot * 32768, &mo, row, h * 256, bars + 8 + mt * 8);
  };
  if (warp == 0) {
    e_expect(bars, 57344);
    e_tma3d(sb, type == 0 ? &mk : &mv, 0, nq * SL, h * 4, bars);
    for (int i = 0; i < 5; i++) load_a(i, i);
  }
  {
    const int gt = blockIdx.x * 256 + threadIdx.x;
    if (gt < 10240) ((uint4*)acc_base())[gt] = make_uint4(0, 0, 0, 0);
    else if (gt < 10242) g_side[gt - 10240 + 156] = 0;
  }
  const float sc = type == 0 ? 0.0625f * 1.4426950408889634f : 1.0f;
  mbar_wait(bars, 0);
  GT(blockIdx.x == 0 && threadIdx.x == 0, 16);
  const uint64_t db = mkdesc(sb, 16, 1024, 1);
  for (int mt = wg; mt < 7; mt += 2) {
    const int slot = mt < 5 ? mt : 6 - mt;
    float d[56];
    mbar_wait(bars + 8 + mt * 8, 0);
    const uint64_t da = mkdesc(abuf + slot * 32768, 16, 1024, 1);
    wg_fence();
    if (type == 0) {
      #pragma unroll
      for (int k = 0; k < 16; k++) {
        if (k == 0) wg_ss112z<0, 0>(d, da, db); else wg_ss112<0, 0>(d, da + (k >> 2) * 512 + (k & 3) * 2, db + (k >> 2) * 896 + (k & 3) * 2);
      }
    } else {
      #pragma unroll
      for (int k = 0; k < 16; k++) {
        if (k == 0) wg_ss112z<1, 0>(d, da, db); else wg_ss112<1, 0>(d, da + k * 128, db + (k >> 2) * 896 + (k & 3) * 2);
      }
    }
    wg_commit();
    wg_wait<0>();
    acc_fence<56>(d);
    if (mt < 2) { bar_sync_id(1 + wg, 128); if ((warp & 3) == 0) load_a(6 - mt, mt); }
    GT(blockIdx.x == 0 && threadIdx.x == 0 && (mt == 0 || mt == 6), mt ? 18 : 17);
    uint4* dst = g_frag[type] + ((size_t)(h * 28 + ((mt + ROT * nq) % 7) * 4 + (warp & 3)) * 28 + 7 * nq) * 32 + lane;
    #pragma unroll
    for (int k = 0; k < 7; k++)
      dst[k * 32] = make_uint4(pack_bf(d[8 * k] * sc, d[8 * k + 1] * sc), pack_bf(d[8 * k + 2] * sc, d[8 * k + 3] * sc),
                               pack_bf(d[8 * k + 4] * sc, d[8 * k + 5] * sc), pack_bf(d[8 * k + 6] * sc, d[8 * k + 7] * sc));
  }
}
#define NOVA 7
#define KRF 20
#define RPE 0
#define FDEP 4
#define NPH 3
#define C2AT 8
#define DUTYL 3
#define DUTYE 3
#define EZ 0
#define DDELAY 0
#define PMARG 100
#define PKP 0
#define PKI 0
#define WEARLY 0
#define PVV 0
#define QAT 7
#define QPIN 5
#define TRN 0
#define PAT 0
#define RDELAY 400
#define NOVB 7
constexpr int XS_SZ = 28672;
constexpr int XA_OFF = 0;
constexpr int YS_OFF = 3 * 8192, YS_SZ = 14336;
constexpr int YT_OFF = YS_OFF + 3 * YS_SZ, YT_SZ = 7168;
constexpr int ZT_OFF = YT_OFF + 3 * YT_SZ;
constexpr int WT_OFF = ZT_OFF + 3 * YT_SZ;
constexpr int WP_OFF = WT_OFF + 4 * 2048;
constexpr int BOV_OFF = WP_OFF + 4 * 1792 + 256;
constexpr int ONES_OFF = BOV_OFF + 4 * NOVB * 512;
constexpr int MEM_OFF = ONES_OFF + 128, MEM_P = 912;
constexpr int AOV_OFF = MEM_OFF + 8 * MEM_P;
constexpr int ZER_OFF = AOV_OFF + 4 * NOVA * 512;
constexpr int DUMP_OFF = ZER_OFF + 128;
constexpr int RXX_OFF = DUMP_OFF + 256;
constexpr int LOC_OFF = RXX_OFF + 1024;
constexpr int RX2_OFF = LOC_OFF + 2048;
constexpr int PS_OFF = RX2_OFF + 5120;
constexpr int R_END = PS_OFF + 5120;
constexpr int BAR_OFF = 204800;
constexpr int TIM_OFF = BAR_OFF + 256;
constexpr int MAIN_SMEM = TIM_OFF + 16384 + 1024;
static_assert(R_END <= BAR_OFF, "smem");
enum { B_MEM1 = 1, B_MEM2, B_C2, B_W, B_RED, B_LOC, B_LOX, B_PAIR };
constexpr uint32_t CNT = 0x41800000u;
constexpr unsigned VFLAG_N = 128, TFLAG_N = 14;
#define TIM(i)

DEVI void sum_send(uint32_t a_loc, int remote, uint32_t r_addr, uint32_t r_bar) {
  const uint4 p0 = lds128(a_loc), p1 = lds128(a_loc + 512), p2 = lds128(a_loc + 1024), p3 = lds128(a_loc + 1536);
#define SUM4(c) ((__uint_as_float(p0.c) + __uint_as_float(p1.c)) + (__uint_as_float(p2.c) + __uint_as_float(p3.c)))
  const uint32_t vm = pack_bf(SUM4(x), SUM4(y)), vx = pack_bf(SUM4(z), SUM4(w));
  asm volatile("{.reg .pred p, e;\nsetp.ne.s32 p, %0, 0;\n"
    "@p st.async.weak.shared::cluster.mbarrier::complete_tx::bytes.u32 [%1+512], %3, [%2];\n"
    "@p st.async.weak.shared::cluster.mbarrier::complete_tx::bytes.u32 [%1], %4, [%2];\n"
    "@!p st.shared.u32 [%1+512], %3;\n@!p st.shared.u32 [%1], %4;\n"
    "bar.warp.sync 0xffffffff;\nelect.sync _|e, 0xffffffff;\nand.pred e, e, !p;\n"
    "@e mbarrier.arrive.expect_tx.shared::cta.b64 _, [%2], 768;\n}" :: "r"(remote), "r"(r_addr), "r"(r_bar), "r"(vm), "r"(vx) : "memory");
}

DEVI float quad_max(float s0, float s1, uint32_t x0, uint32_t x1, uint32_t x2, uint32_t x3) {
  uint32_t xm; asm("{.reg .b32 a, b; max.bf16x2 a, %1, %2; max.bf16x2 b, %3, %4; max.bf16x2 %0, a, b;}" : "=r"(xm) : "r"(x0), "r"(x1), "r"(x2), "r"(x3));
  const float mx = fmaxf(fmaxf(bf_lo(xm), bf_hi(xm)), fmaxf(s0, s1));
  const float m1 = __shfl_xor_sync(0xffffffffu, mx, 1), m2 = __shfl_xor_sync(0xffffffffu, mx, 2), m3 = __shfl_xor_sync(0xffffffffu, mx, 3);
  return fmaxf(fmaxf(mx, m1), fmaxf(m2, m3));
}
DEVI void probs_sum(uint32_t sb, int s, int lane, float (&e)[5][4]) {
  mbar_wait(sb + BAR_OFF + 96 + (s & 1) * 8, (s >> 1) & 1);
  const int dg = (lane >> 2) - 2 * (lane & 3);
  const uint32_t id = dg == 0 ? 0x3f80u : dg == 1 ? 0x3f800000u : 0u;
  #pragma unroll
  for (int i = 0; i < 5; i++) {
    uint32_t b0, b1, b2, b3;
    ldsm4t(sb + RX2_OFF + (s & 1) * 2560 + i * 512 + lane * 16, b0, b1, b2, b3);
    mma16816z(e[i], id, id, id, id, b0, b1); mma16816(e[i], id, id, id, id, b2, b3);
  }
}
DEVI void probs_fin(uint32_t sb, int s, int j, int lane, float (&e)[5][4]) {
  const int lim = 8 * j + (lane >> 2) - 2 * (lane & 3);
  float mx = fmaxf(e[0][0], e[0][1]);
  #pragma unroll
  for (int i = 1; i < 5; i++) {
    if (8 * i - 8 > lim) e[i][0] = -INFINITY;
    if (8 * i - 7 > lim) e[i][1] = -INFINITY;
    mx = fmaxf(mx, fmaxf(e[i][0], e[i][1]));
  }
  { const float m1 = __shfl_xor_sync(0xffffffffu, mx, 1), m2 = __shfl_xor_sync(0xffffffffu, mx, 2), m3 = __shfl_xor_sync(0xffffffffu, mx, 3);
    mx = fmaxf(fmaxf(mx, m1), fmaxf(m2, m3)); }
  #pragma unroll
  for (int i = 0; i < 5; i++) { e[i][0] = ex2(e[i][0] - mx); e[i][1] = ex2(e[i][1] - mx); }
  float sum = (((e[0][0] + e[0][1]) + (e[1][0] + e[1][1])) + ((e[2][0] + e[2][1]) + (e[3][0] + e[3][1]))) + (e[4][0] + e[4][1]);
  { const float s1 = __shfl_xor_sync(0xffffffffu, sum, 1), s2 = __shfl_xor_sync(0xffffffffu, sum, 2), s3 = __shfl_xor_sync(0xffffffffu, sum, 3);
    sum = (sum + s1) + (s2 + s3); }
  const float inv = rcpf(sum);
  #pragma unroll
  for (int i = 0; i < 5; i++) sts32(sb + PS_OFF + (s & 7) * 640 + i * 128 + lane * 4, pack_bf(e[i][0] * inv, e[i][1] * inv));
}

DEVI void r_score(const bf16* mem0, uint32_t sb, int h, int j, int side, int warp, int lane_) {
  const int q = warp;
  uint32_t aw[49 - NOVA][4];
  int lane = lane_;
  constexpr int UA[7] = {0, 3, 6, 9, 2, 8, 5}, UB[7] = {1, 4, 7, 10, 12, 13, 11};
  #pragma unroll
  for (int i = 0; i < 49; i++) {
    const uint2* base = (const uint2*)(g_frag[0] + ((size_t)(h * 28 + 7 * j + i % 7) * 28 + 7 * q) * 32 + lane);
    uint2 lo = base[(UA[i / 7] >> 1) * 64 + (UA[i / 7] & 1)], hi = base[(UB[i / 7] >> 1) * 64 + (UB[i / 7] & 1)];
    if (i >= NOVA) { aw[i >= NOVA ? i - NOVA : 0][0] = lo.x; aw[i >= NOVA ? i - NOVA : 0][1] = lo.y; aw[i >= NOVA ? i - NOVA : 0][2] = hi.x; aw[i >= NOVA ? i - NOVA : 0][3] = hi.y; }
    else sts128(sb + AOV_OFF + (q * NOVA + i) * 512 + lane * 16, make_uint4(lo.x, lo.y, hi.x, hi.y));
  }
  uint4 w[4];
  {
    uint32_t t[14];
    #pragma unroll
    for (int u = 0; u < 14; u++) t[u] = *(const uint32_t*)(mem0 + (lane >> 2) * D + SL * q + 8 * u + 2 * (lane & 3));
    #pragma unroll
    for (int i = 0; i < 4; i++) { w[i].x = t[3 * i]; w[i].y = t[3 * i + 1]; w[i].z = t[3 * i + 2]; w[i].w = ((t[12 + (i >> 1)] >> ((i & 1) * 16)) & 0xffffu) | CNT; }
  }
  const uint32_t d2m = sb + BAR_OFF + 88;
  const uint32_t a_m = sb + MEM_OFF + (lane & 7) * MEM_P + (lane >> 3) * 16;
  const char* rp = acc_base();
  int sl = 0;
  uint32_t a_s0, a_s1, a_s2;
  uint4 ov[NOVA];
  auto st_addr = [&]() {
    const uint32_t l3 = lane >= 24;
    a_s0 = a_m + l3 * 144; a_s1 = a_m + l3 * 80; a_s2 = a_m + l3 * 64;
    asm volatile("" : "+r"(a_s0), "+r"(a_s1), "+r"(a_s2));
    #pragma unroll
    for (int i = 0; i < NOVA; i++) ov[i] = lds128(sb + AOV_OFF + (q * NOVA + i) * 512 + lane * 16);
  };
  st_addr();
  for (int s = 0; s < NSEG; s++) {
    if (__builtin_expect(__any_sync(0xffffffffu, (w[0].w & w[1].w & w[2].w & w[3].w & CNT) != CNT), 0)) {
      int spin = 0;
      do {
        #pragma unroll
        for (int i = 0; i < 4; i++) w[i] = ldg128_relaxed(rp + i * 1024);
        if (++spin > SPIN_LIMIT) __trap();
      } while (__any_sync(0xffffffffu, (w[0].w & w[1].w & w[2].w & w[3].w & CNT) != CNT));
    }
    TIM(0);
    uint32_t mb[14];
    mb[0] = w[0].x; mb[1] = w[0].y; mb[2] = w[1].x; mb[3] = w[1].y; mb[4] = w[2].x; mb[5] = w[2].y; mb[6] = w[3].x; mb[7] = w[3].y;
    mb[8] = w[0].z; mb[9] = __byte_perm(w[0].w, w[1].w, 0x5410); mb[10] = w[2].z; mb[11] = __byte_perm(w[2].w, w[3].w, 0x5410); mb[12] = w[1].z; mb[13] = w[3].z;
    float acc[7][4], se[4], so[4];
    uint32_t qa[14], zr;
    {
      stsm4(a_s0 + 224 * q, mb[0], mb[1], mb[8], mb[9]); stsm4(a_s1 + 224 * q + 48, mb[2], mb[3], mb[12], mb[13]);
      stsm4(a_s2 + 224 * q + 96, mb[4], mb[5], mb[10], mb[11]); stsm2(a_m + 224 * q + 144, mb[6], mb[7]);
      asm volatile("bar.arrive %0, 64;" :: "r"(B_PAIR + q) : "memory");
      zr = lds32(sb + ZER_OFF);
    }
    OPAQUE(lane);
    #pragma unroll
    for (int i = 0; i < 49; i++) {
      const int m = i % 7, ks = i / 7, f = i >= NOVA ? i - NOVA : 0;
      if (i == QAT) {
        bar_sync<B_MEM2, 128>();
        const uint32_t a = a_m + 224 * j;
        ldsm4(a, qa[0], qa[1], qa[2], qa[3]); ldsm4(a + 64, qa[4], qa[5], qa[6], qa[7]); ldsm4(a + 128, qa[8], qa[9], qa[10], qa[11]); ldsm2(a + 192, qa[12], qa[13]);
        if (QPIN) mb[2 * QPIN] |= qa[13] & zr;
      }
      if (m == 0 && ks >= 1 && ks < 6 && ((FDEP >> ks) & 1)) {
        uint32_t t = 0;
        #pragma unroll
        for (int e = 0; e < 7; e++) t |= __float_as_uint(acc[e][0]);
        mb[2 * (ks + 1)] |= t & zr;
      }
      if (i < NOVA) mma16816z(acc[m], ov[i < NOVA ? i : 0].x, ov[i < NOVA ? i : 0].y, ov[i < NOVA ? i : 0].z, ov[i < NOVA ? i : 0].w, mb[0], mb[1]);
      else if (ks == 0) mma16816z(acc[m], aw[f][0], aw[f][1], aw[f][2], aw[f][3], mb[0], mb[1]);
      else mma16816(acc[m], aw[f][0], aw[f][1], aw[f][2], aw[f][3], mb[2 * ks], mb[2 * ks + 1]);
    }
    {
      const uint32_t a_rp = sb + YS_OFF + sl * YS_SZ + (4 + q) * 1792 + lane * 16;
      const uint32_t a_rt = sb + YS_OFF + sl * YS_SZ + (4 + q) * 1792 + ((lane & 7) | ((lane & 8) << 1) | ((lane & 16) >> 1)) * 16;
      float te[4], to[4];
      uint32_t tb[14];
      #pragma unroll
      for (int mm = 0; mm < 7; mm += 2) {
        if (mm < 6) {
          stsm4(a_rp + mm * 256, pack_bf(acc[mm][0], acc[mm][1]), pack_bf(acc[mm][2], acc[mm][3]), pack_bf(acc[mm + 1][0], acc[mm + 1][1]), pack_bf(acc[mm + 1][2], acc[mm + 1][3]));
          if (mm == C2AT) bar_arrive<B_C2, 256>();
          __syncwarp();
          ldsm4t(a_rt + mm * 256, tb[2 * mm], tb[2 * mm + 1], tb[2 * mm + 2], tb[2 * mm + 3]);
        } else {
          stsm2(a_rp + 1536, pack_bf(acc[6][0], acc[6][1]), pack_bf(acc[6][2], acc[6][3]));
          if (mm == C2AT) bar_arrive<B_C2, 256>();
          __syncwarp();
          ldsm2t(a_rp + 1536, tb[12], tb[13]);
        }
      }
      mma16816z(se, qa[0], qa[1], qa[2], qa[3], tb[0], tb[1]); mma16816z(so, qa[0], qa[1], qa[2], qa[3], tb[2], tb[3]);
      mma16816z(te, qa[4], qa[5], qa[6], qa[7], tb[4], tb[5]); mma16816z(to, qa[4], qa[5], qa[6], qa[7], tb[6], tb[7]);
      mma16816(se, qa[8], qa[9], qa[10], qa[11], tb[8], tb[9]); mma16816(so, qa[8], qa[9], qa[10], qa[11], tb[10], tb[11]);
      mma1688(te, qa[12], qa[13], tb[12]); mma1688(to, qa[12], qa[13], tb[13]);
      sts64f(sb + LOC_OFF + q * 512 + lane * 16, (se[0] + so[2]) + (te[0] + to[2]), (se[1] + so[3]) + (te[1] + to[3]));
      if (C2AT == 8) bar_arrive<B_C2, 256>();
    }
    TIM(1);
    const uint32_t rr = (j + q) & 3;
    const uint32_t l_addr = sb + RXX_OFF + j * 128 + lane * 4;
    uint32_t r_addr = mapa(l_addr, rr), r_bar = mapa(d2m, rr), a_loc = sb + LOC_OFF + lane * 16;
    asm volatile("" : "+r"(r_addr), "+r"(r_bar), "+r"(a_loc));
    bar_sync<B_LOC, 256>();
    {
      sum_send(a_loc, q != 0, r_addr, r_bar);
    }
    TIM(2);
    const uint32_t zb = sb + ZT_OFF + sl * YT_SZ;
    const int r8 = lane & 7, i4 = lane >> 3;
    const uint32_t c3 = 8 * (12 + (q >> 1)) + r8 + (q & 1);
    const uint32_t ones = sb + ONES_OFF + ((q & 1) ? 0 : 16);
    uint32_t zf[4][4];
    #pragma unroll
    for (int i = 0; i < 3; i++) ldsm4(zb + i4 * 1792 + (8 * (3 * q + i) + r8) * 16, zf[i][0], zf[i][1], zf[i][2], zf[i][3]);
    ldsm4((r8 & 1) ? ones : zb + i4 * 1792 + c3 * 16, zf[3][0], zf[3][1], zf[3][2], zf[3][3]);
    const uint32_t goff = i4 * 256 + r8 * 16;
    const char* accw = acc_base() + (acc_off(s + 1, j, side) + q * 1024) + goff;
    uint32_t a_w = sb + WP_OFF + i4 * 1792 + (24 * q + r8) * 16;
    uint32_t a_w3 = (r8 & 1) ? (i4 == 0 ? ones : sb + ZER_OFF + ((q & 1) ? 0 : 16)) : sb + WP_OFF + i4 * 1792 + c3 * 16;
    uint32_t a_rx = sb + RXX_OFF + lane * 16;
    asm volatile("" : "+r"(a_w), "+r"(a_w3), "+r"(a_rx), "+l"(accw));
    fence_async_smem();
    TIM(3);
    mbar_wait(d2m, s & 1);
    TIM(4);
    uint32_t x0, x1, x2, x3, v0, v1, v2, v3;
    ldsm4(a_rx + 512, v0, v1, v2, v3);
    ldsm4(a_rx, x0, x1, x2, x3);
    const float s0 = (bf_lo(v0) + bf_lo(v1)) + (bf_lo(v2) + bf_lo(v3)), s1 = (bf_hi(v0) + bf_hi(v1)) + (bf_hi(v2) + bf_hi(v3));
    const float mx = quad_max(s0, s1, x0, x1, x2, x3);
    bar_sync<B_W, 256>();
    uint32_t wf[4][4];
    ldsm4(a_w3, wf[3][0], wf[3][1], wf[3][2], wf[3][3]);
    #pragma unroll
    for (int i = 2; i >= 0; i--) ldsm4(a_w + i * 128, wf[i][0], wf[i][1], wf[i][2], wf[i][3]);
    const uint32_t p1 = pack_bf(ex2(bf_lo(x0) - mx), ex2(bf_hi(x0) - mx)), p2 = pack_bf(ex2(bf_lo(x1) - mx), ex2(bf_hi(x1) - mx));
    const uint32_t p3 = pack_bf(ex2(bf_lo(x2) - mx), ex2(bf_hi(x2) - mx)), p4 = pack_bf(ex2(bf_lo(x3) - mx), ex2(bf_hi(x3) - mx));
    const uint32_t p0 = pack_bf(ex2(s0 - mx), ex2(s1 - mx));
    TIM(5);
    float o[4][4], u[4][4];
    #pragma unroll
    for (int i = 3; i >= 0; i--) mma16816z(o[i], p1, p1, p2, p2, zf[i][0], zf[i][1]);
    #pragma unroll
    for (int i = 3; i >= 0; i--) mma16816(o[i], p3, p3, p4, p4, zf[i][2], zf[i][3]);
    #pragma unroll
    for (int i = 3; i >= 0; i--) { if (PVV) mma16816z(u[i], p0, p0, p0, p0, wf[i][0], wf[i][1]); else mma16816(o[i], p0, p0, p0, p0, wf[i][0], wf[i][1]); }
    #pragma unroll
    for (int i = 3; i >= 0; i--) mma16816(PVV ? u[i] : o[i], p0, p0, p0, p0, wf[i][2], wf[i][3]);
    if (PVV) {
      #pragma unroll
      for (int i = 3; i >= 0; i--) { o[i][0] += u[i][0]; o[i][1] += u[i][1]; }
    }
    const float inv = rcpf(o[3][1]);
    uint32_t w0 = pack_bf(o[0][0] * inv, o[0][1] * inv), w1 = pack_bf(o[1][0] * inv, o[1][1] * inv), w2 = pack_bf(o[2][0] * inv, o[2][1] * inv), w3 = pack_bf(o[3][0] * inv, 1.0f);
    asm volatile("red.relaxed.gpu.global.add.noftz.v4.bf16x2 [%0], {%1,%2,%3,%4};" :: "l"(accw), "r"(w0), "r"(w1), "r"(w2), "r"(w3) : "memory");
    const unsigned tp = clk32() + RDELAY;
    bar_arrive<B_RED, 256>();
    if (s == NSEG - 1) break;
    TIM(6);
    GT(h == 1 && j == 1 && q == 0 && ((s & 7) == 0 || s < 8), (s & 7) == 0 ? 8 + (s >> 3) : 24 + s);
    rp = acc_base() + acc_off(s + 1, q, side) + goff;
    if (++sl == 3) sl = 0;
    asm volatile("" : "+l"(rp));
    OPAQUE(lane);
    st_addr();
    delay_until(tp);
    TIM(7);
    #pragma unroll
    for (int i = 0; i < 4; i++) w[i] = ldg128_relaxed(rp + i * 1024);
  }
}

DEVI void r_value(const CUtensorMap* xmap, const CUtensorMap* ymap, const CUtensorMap* zmap, uint32_t sb, int h, int j, int side, int warp, int lane) {
  const int v = warp - 4;
  uint32_t bw[49 - NOVB][4];
  #pragma unroll
  for (int i = 0; i < 49; i++) {
    const uint4 x = g_frag[1][((size_t)(h * 28 + 7 * j + i % 7) * 28 + 7 * v + i / 7) * 32 + lane];
    if (i < 49 - NOVB) { bw[i < 49 - NOVB ? i : 0][0] = x.x; bw[i < 49 - NOVB ? i : 0][1] = x.y; bw[i < 49 - NOVB ? i : 0][2] = x.z; bw[i < 49 - NOVB ? i : 0][3] = x.w; }
    else sts128(sb + BOV_OFF + (v * NOVB + i - (49 - NOVB)) * 512 + lane * 16, x);
  }
  const uint32_t tfull = sb + BAR_OFF;
  unsigned* const vflag = vflag_ptr(side);
  const unsigned* const tflag = tflag_ptr(side) + h;
  auto loads = [&](int s, int sl, bool late) {
    if (v == 1) {
      if (__builtin_expect(late, 0)) { wait_flag<0>(tflag + s * NH, TFLAG_N); fence_async_global(); }
      e_g2s(sb + YT_OFF + sl * YT_SZ, g_yt + (size_t)((s * NH + h) * 4 + j) * PL, YT_SZ, tfull + sl * 8);
      e_tma3d(sb + ZT_OFF + sl * YT_SZ, zmap, 0, 4 * j, s * 80 + h * 4, tfull + sl * 8);
      e_tma3d(sb + YS_OFF + sl * YS_SZ, ymap, 0, 4 * j, s * 64 + h * 4, tfull + sl * 8);
    } else {
      e_expect(tfull + sl * 8, 3 * YT_SZ + 8192);
      e_tma2d(sb + XA_OFF + sl * 8192, xmap, SL * j, s * SEG, tfull + sl * 8);
      e_tma2d(sb + XA_OFF + sl * 8192 + 4096, xmap, SL * j + 64, s * SEG, tfull + sl * 8);
    }
  };
  auto put_w = [&](int s) { e_s2g(g_vt + (size_t)(s * 80 + 64 + h) * PL + SL * j * 8, sb + WT_OFF + (s & 3) * 2048, 1792); };
  auto put_p = [&](int s) { e_s2g(g_p + (size_t)((s * NH + h) * 4 + j) * 320, sb + PS_OFF + (s & 7) * 640, 640); };
  if (v == 1 || v == 2) { loads(0, 0, true); loads(1, 1, true); }
  int nl = 2;
  const uint32_t d2t = sb + BAR_OFF + 96;
  unsigned tf = 0;
  auto sum4 = [&](uint32_t src, uint32_t dst) {
    const uint32_t a = src + lane * 16;
    const uint4 u0 = lds128(a), u1 = lds128(a + 1792), u2 = lds128(a + 3584), u3 = lds128(a + 5376);
#define RSUM(c) pack_bf((bf_lo(u0.c) + bf_lo(u1.c)) + (bf_lo(u2.c) + bf_lo(u3.c)), (bf_hi(u0.c) + bf_hi(u1.c)) + (bf_hi(u2.c) + bf_hi(u3.c)))
    sts128(dst + lane * 16, make_uint4(RSUM(x), RSUM(y), RSUM(z), RSUM(w)));
  };
  int sl = 0, ph = 0;
  uint32_t yb[14];
  auto load_yb = [&](int sl) {
    const uint32_t ay = sb + YT_OFF + sl * YT_SZ + v * 1792, ap = ay + ((lane & 7) | ((lane & 8) << 1) | ((lane & 16) >> 1)) * 16;
    ldsm4t(ap, yb[0], yb[1], yb[2], yb[3]); ldsm4t(ap + 512, yb[4], yb[5], yb[6], yb[7]);
    ldsm4t(ap + 1024, yb[8], yb[9], yb[10], yb[11]); ldsm2t(ay + 1536 + lane * 16, yb[12], yb[13]);
  };
  GT(h == 1 && j == 1 && v == 0 && lane == 0, 20);
  mbar_wait(tfull, 0);
  GT(h == 1 && j == 1 && v == 0 && lane == 0, 21);
  load_yb(0);
  for (int s = 0; s < NSEG; s++) {
    OPAQUE(lane);
    uint32_t qa[14];
    const int sn = sl == 2 ? 0 : sl + 1;
    float e[5][4];
    uint32_t aj = sb + MEM_OFF + (lane & 7) * MEM_P + (lane >> 3) * 16 + 224 * v;
    OPAQUE(aj);
    bar_sync_id(B_PAIR + v, 64);
    TIM(0);
    {
      float se[4], so[4], te[4], to[4];
      ldsm4(aj, qa[0], qa[1], qa[2], qa[3]); ldsm4(aj + 64, qa[4], qa[5], qa[6], qa[7]);
      ldsm4(aj + 128, qa[8], qa[9], qa[10], qa[11]); ldsm2(aj + 192, qa[12], qa[13]);
      mma16816z(se, qa[0], qa[1], qa[2], qa[3], yb[0], yb[1]); mma16816z(so, qa[0], qa[1], qa[2], qa[3], yb[2], yb[3]);
      mma16816z(te, qa[4], qa[5], qa[6], qa[7], yb[4], yb[5]); mma16816z(to, qa[4], qa[5], qa[6], qa[7], yb[6], yb[7]);
      mma16816(se, qa[8], qa[9], qa[10], qa[11], yb[8], yb[9]); mma16816(so, qa[8], qa[9], qa[10], qa[11], yb[10], yb[11]);
      mma1688(te, qa[12], qa[13], yb[12]); mma1688(to, qa[12], qa[13], yb[13]);
      sts64f(sb + LOC_OFF + v * 512 + lane * 16 + 8, ((se[0] + so[2]) + (te[0] + to[2])), ((se[1] + so[3]) + (te[1] + to[3])));
      bar_arrive<B_LOC, 256>();
    }
    if (v == 2) { if (s + 2 < NSEG) loads(s + 2, sl == 0 ? 2 : sl - 1, false); }
    else if (v == 1) {
      const unsigned late = __ballot_sync(0xffffffffu, tf < TFLAG_N);
      if (__builtin_expect(nl == s + 1 && nl < NSEG, 0)) { loads(s + 1, sn, late & 1); nl = s + 2; }
      if (s + 2 < NSEG && !(late & 2)) { loads(s + 2, sl == 0 ? 2 : sl - 1, false); nl = s + 3; }
    }
    else {
      if (v == 0) { e_s2g(acc_base() + acc_off(s + 4, j, side) + h * 256, sb + ZER_OFF, 128); if (s > 0) put_w(s - 1); }
      else if (s > 1) put_p(s - 2);
      bulk_commit();
    }
    TIM(1);
    {
      uint4 ov[NOVB];
      #pragma unroll
      for (int i = 0; i < NOVB; i++) ov[i] = lds128(sb + BOV_OFF + (v * NOVB + i) * 512 + lane * 16);
      const uint32_t zr = lds32(sb + ZER_OFF);
      bar_sync<B_C2, 256>();
      asm volatile("pmevent 0;");
      TIM(2);
      float acc[7][4];
      #pragma unroll
      for (int n = 0; n < 49; n++) {
        const int i = 48 - n, m = i % 7, ks = i / 7, f = i < 49 - NOVB ? i : 0;
        if (n == 14) {
          uint32_t t = 0;
          #pragma unroll
          for (int e = 0; e < 7; e++) t |= __float_as_uint(acc[e][0]);
          qa[6] |= t & zr;
        }
        if (i >= 49 - NOVB) { const uint4 x = ov[i >= 49 - NOVB ? i - (49 - NOVB) : 0]; if (ks == 6) mma16816z(acc[m], x.x, x.y, x.z, x.w, qa[12], qa[13]); else mma16816(acc[m], x.x, x.y, x.z, x.w, qa[2 * ks], qa[2 * ks + 1]); }
        else if (ks == 6) mma16816z(acc[m], bw[f][0], bw[f][1], bw[f][2], bw[f][3], qa[12], qa[13]);
        else mma16816(acc[m], bw[f][0], bw[f][1], bw[f][2], bw[f][3], qa[2 * ks], qa[2 * ks + 1]);
      }
      const uint32_t a = sb + WP_OFF + v * 1792 + lane * 16;
      stsm2(a + 1536, pack_bf(acc[6][0], acc[6][1]), pack_bf(acc[6][2], acc[6][3]));
      #pragma unroll
      for (int mm = 4; mm >= 0; mm -= 2)
        stsm4(a + mm * 256, pack_bf(acc[mm][0], acc[mm][1]), pack_bf(acc[mm][2], acc[mm][3]), pack_bf(acc[mm + 1][0], acc[mm + 1][1]), pack_bf(acc[mm + 1][2], acc[mm + 1][3]));
      bar_arrive<B_W, 256>();
      #pragma unroll
      for (int i = 0; i < 5; i++) e[i][0] = e[i][1] = 0.f;
      if (v == 3 && s > 0) probs_sum(sb, s - 1, lane, e);
      bulk_wait<0>();
      red_add_if(lane == 0 && (v == 0 ? s >= 1 : v == 3 && s >= 2), vflag + (s - (v ? 2 : 1)) * 16, 1);
      if (s < NSEG - 1) mbar_wait(tfull + sn * 8, sn ? ph : ph ^ 1);
      TIM(3);
    }
    bar_sync<B_RED, 256>();
    TIM(4);
    {
      float d[32];
      const uint64_t da = mkdesc(sb + XA_OFF + sl * 8192, 16, 512, 1), db = mkdesc(sb + YS_OFF + sl * YS_SZ, 128, 1792, 0);
      wg_fence();
      #pragma unroll
      for (int k = 0; k < 7; k++) { if (k == 0) wg_ss64z<0, 1>(d, da, db); else wg_ss64<0, 1>(d, da + (k >> 2) * 256 + (k & 3) * 2, db + k * 16); }
      wg_commit();
      OPAQUE(lane);
      const uint32_t ra = mapa(sb + RX2_OFF + (s & 1) * 2560 + j * 128 + lane * 4, v), rb = mapa(d2t + (s & 1) * 8, v);
      if (v == 3) probs_fin(sb, s - 1, j, lane, e);
      else {
        sum4(sb + WP_OFF + v * 512, sb + WT_OFF + (s & 3) * 2048 + v * 512);
        if (v == 2) sum4(sb + WP_OFF + 1536, sb + WT_OFF + (s & 3) * 2048 + 1536);
      }
      wg_wait<0>();
      acc_fence<32>(d);
      uint32_t m[5];
      m[0] = pack_bf((d[16] + d[20]) + (d[24] + d[28]), (d[17] + d[21]) + (d[25] + d[29]));
      #pragma unroll
      for (int i = 0; i < 4; i++) m[1 + i] = pack_bf(d[4 * i], d[4 * i + 1]);
      if (v != j) {
        #pragma unroll
        for (int i = 0; i < 5; i++) if (i <= v + 1) asm volatile("st.async.weak.shared::cluster.mbarrier::complete_tx::bytes.u32 [%0], %1, [%2];" :: "r"(ra + i * 512), "r"(m[i]), "r"(rb) : "memory");
      } else {
        #pragma unroll
        for (int i = 0; i < 5; i++) sts32(ra + i * 512, m[i]);
        __syncwarp();
        e_expect(rb, 384 * (j + 2));
      }
      fence_async_smem();
      if (v == 0) bar_sync<B_LOX, 96>(); else if (v < 3) bar_arrive<B_LOX, 96>();
      if (v == 1) tf = ldg_relaxed(tflag + (s + 2 + (lane & 1)) * NH);
      load_yb(sn);
    }
    if (++sl == 3) { sl = 0; ph ^= 1; }
    TIM(5);
  }
  if (v == 0) { put_w(NSEG - 1); bulk_commit(); bulk_wait<0>(); red_add_if(lane == 0, vflag + (NSEG - 1) * 16, 1); }
  if (v == 3) {
    __syncwarp();
    put_p(NSEG - 2); bulk_commit();
    float e[5][4];
    probs_sum(sb, NSEG - 1, lane, e); probs_fin(sb, NSEG - 1, j, lane, e); fence_async_smem(); __syncwarp();
    put_p(NSEG - 1); bulk_commit();
    bulk_wait<1>(); red_add_if(lane == 0, vflag + (NSEG - 2) * 16, 1);
    bulk_wait<0>(); red_add_if(lane == 0, vflag + (NSEG - 1) * 16, 1);
  }
}

constexpr int HYS_OFF = 4 * XS_SZ;

#define NFAST 4
#define RWAIT 0
#define YRF 21
#define YLEAD 64
constexpr int NYCL = 14, HOV_OFF = HYS_OFF + 32768;
static_assert(HOV_OFF + 2 * (28 - YRF) * 2048 <= BAR_OFF, "smem");
DEVI void h_keys(const CUtensorMap* xmap, uint32_t sb, int hid, int r, int side, int warp, int lane) {
  const int wg = warp >> 2, w = warp & 3;
  const uint32_t xfull = sb + BAR_OFF + 24, xempty = sb + BAR_OFF + 56, hov = sb + HOV_OFF + wg * (28 - YRF) * 2048;
  const int u0 = hid * 2, h0 = u0 / 7, h1 = (u0 + 1) / 7;
  const unsigned* vflag = vflag_ptr(side);
  auto load_x = [&](int s) {
    if (s >= 4) mbar_wait(xempty + (s & 3) * 8, ((s >> 2) - 1) & 1);
    if (s >= YLEAD) wait_flag(vflag + (s - YLEAD) * 16, 1);
    e_expect(xfull + (s & 3) * 8, XS_SZ);
    e_tma3d_mc(sb + (s & 3) * XS_SZ + r * 7168, xmap, 0, s * SEG + 8 * r, 0, xfull + (s & 3) * 8, 15);
  };
  if (warp == 1) for (int i = 0; i < 3; i++) load_x(i);
  uint32_t a0[28][4], a1[YRF][4];
  const uint4* fr = g_frag[wg] + ((size_t)(u0 * 4 + w) * 28) * 32 + lane;
  #pragma unroll
  for (int ks = 27; ks >= 0; ks--) {
    const uint4 x = fr[(112 + ks) * 32];
    if (ks < YRF) { a1[ks < YRF ? ks : 0][0] = x.x; a1[ks < YRF ? ks : 0][1] = x.y; a1[ks < YRF ? ks : 0][2] = x.z; a1[ks < YRF ? ks : 0][3] = x.w; }
    else stsm4(hov + (ks - YRF) * 2048 + (lane >> 4) * 1024 + w * 256 + (lane & 15) * 16, x.x, x.y, x.z, x.w);
  }
  #pragma unroll
  for (int ks = 0; ks < 28; ks++) { const uint4 x = fr[ks * 32]; a0[ks][0] = x.x; a0[ks][1] = x.y; a0[ks][2] = x.z; a0[ks][3] = x.w; }
  fence_async_smem();
  bar_sync_id(1 + wg, 128);
  bf16* dst0 = (wg ? g_vt : g_yt) + (h0 * 4 + w) * PL + 512 * (u0 - 7 * h0);
  bf16* dst1 = (wg ? g_vt : g_yt) + (h1 * 4 + w) * PL + 512 * (u0 + 1 - 7 * h1);
  const int sstr = (wg ? 80 : 64) * PL;
  GT(hid == 0 && threadIdx.x == 0, 22);
  if (wg == 1) bar_arrive<3, 256>();
  for (int s = 0; s < NSEG; s++) {
    float z0[16], z1[16];
    mbar_wait(xfull + (s & 3) * 8, (s >> 2) & 1);
    bar_sync_id(3 + wg, 256);
    const uint64_t db = mkdesc(sb + (s & 3) * XS_SZ, 16, 7168, 1), da = mkdesc(hov, 1024, 128, 0);
    wg_fence();
    #pragma unroll
    for (int ks = 0; ks < 28; ks++) {
      const uint64_t d = db + (ks >> 2) * 64 + (ks & 3) * 2;
      if (ks == 0) { wg_rs32z<0>(z0, a0[0], d); wg_rs32z<0>(z1, a1[0], d); }
      else { wg_rs32<0>(z0, a0[ks], d); if (ks < YRF) wg_rs32<0>(z1, a1[ks < YRF ? ks : 0], d); else wg_ss32<0, 0>(z1, da + (ks - YRF) * 128, d); }
    }
    wg_commit();
    if (wg == 0 || s < NSEG - 1) asm volatile("bar.arrive %0, 256;" :: "r"(4 - wg) : "memory");
    wg_wait<0>();
    acc_fence<16>(z0); acc_fence<16>(z1);
    OPAQUE(lane);
    const uint32_t st = sb + HYS_OFF + (wg * 2 + (s & 1)) * 8192, az = st + (lane >> 4) * 1024 + (16 * w + (lane & 15)) * 16;
    stsm4(az, pack_bf(z0[0], z0[1]), pack_bf(z0[2], z0[3]), pack_bf(z0[4], z0[5]), pack_bf(z0[6], z0[7]));
    stsm4(az + 2048, pack_bf(z0[8], z0[9]), pack_bf(z0[10], z0[11]), pack_bf(z0[12], z0[13]), pack_bf(z0[14], z0[15]));
    stsm4(az + 4096, pack_bf(z1[0], z1[1]), pack_bf(z1[2], z1[3]), pack_bf(z1[4], z1[5]), pack_bf(z1[6], z1[7]));
    stsm4(az + 6144, pack_bf(z1[8], z1[9]), pack_bf(z1[10], z1[11]), pack_bf(z1[12], z1[13]), pack_bf(z1[14], z1[15]));
    fence_async_smem();
    unsigned* fl = tflag_ptr(side) + s * NH + (lane ? h1 : h0);
    bulk_wait<0>();
    bar_sync_id(1 + wg, 128);
    e_s2g(dst0 + (size_t)s * sstr, st + w * 1024, 1024);
    e_s2g(dst1 + (size_t)s * sstr, st + 4096 + w * 1024, 1024);
    bulk_commit();
    if (w == 0 && lane < 4) mbar_arrive_remote(mapa(xempty + (s & 3) * 8, lane));
    red_add_if(w == 2 && s > NFAST && lane < 2, fl - NH, 1);
    if (s < NFAST || s == NSEG - 1) { bulk_wait<0>(); bar_sync_id(1 + wg, 128); red_add_if(w == 2 && lane < 2, fl, 1); }
    __syncwarp();
    GT(hid == 0 && threadIdx.x == 128 && s == 0, 23);
    if (warp == 1 && s + 3 < NSEG) load_x(s + 3);
  }
}

constexpr int FO_P = 144;
template <int NT> struct Fin {
  static constexpr int ST = NT * 4096, NS = NT == 7 ? 5 : 20, P_OFF = NS * ST, O_OFF = P_OFF + 40960, B_OFF = O_OFF + 8 * 32 * 48, SMEM = B_OFF + 512 + 1024;
};
template <int NT>
__global__ void __launch_bounds__(288, 1) finish_kernel(const __grid_constant__ CUtensorMap vmap, bf16* __restrict__ out, int s0, int s1) {
  using F = Fin<NT>;
  extern __shared__ __align__(1024) char smem_raw[];
  const uint32_t sb = (smem_u32(smem_raw) + 1023) & ~1023u;
  const int warp = __shfl_sync(0xffffffffu, threadIdx.x >> 5, 0), lane = threadIdx.x & 31;
  const uint32_t full = sb + F::B_OFF, empty = full + 160, pfull = full + 320, pempty = full + 328;
  const int t0 = NT == 7 ? 0 : blockIdx.x % 7, sfirst = s0 + (NT == 7 ? blockIdx.x : blockIdx.x / 7), sstep = NT == 7 ? gridDim.x : NSEG;
  asm volatile("griddepcontrol.launch_dependents;");
  if (threadIdx.x == 0) {
    for (int i = 0; i < F::NS; i++) { mbar_init(full + i * 8, 1); mbar_init(empty + i * 8, 8); }
    mbar_init(pfull, 1); mbar_init(pempty, 8);
    asm volatile("fence.mbarrier_init.release.cluster;" ::: "memory");
  }
  __syncthreads();
  int slot = 0, ph = 0, par = 0;
  if (warp == 8) {
    const int side = rec_side();
    for (int s = sfirst; s < s1; s += sstep, par ^= 1) {
      wait_flag(tflag_ptr(side) + s * NH + (lane & 15), TFLAG_N);
      fence_async_global();
      #pragma unroll 1
      for (int i = 0; i < 20; i++) {
        if (i == (F::NS < 16 ? F::NS : 16)) {
          wait_flag(vflag_ptr(side) + s * 16, VFLAG_N);
          fence_async_global();
          GT(t0 == 0 && lane == 0 && (s & 7) == 7, 200 + (s >> 3));
          mbar_wait(pempty, par ^ 1);
          e_expect(pfull, 40960);
          e_g2s(sb + F::P_OFF, g_p + (size_t)s * 80 * 256, 40960, pfull);
        }
        mbar_wait(empty + slot * 8, ph ^ 1);
        e_expect(full + slot * 8, F::ST);
        if (NT == 7) e_g2s(sb + slot * F::ST, g_vt + (size_t)(s * 80 + i * 4) * PL, F::ST, full + slot * 8);
        else e_tma3d(sb + slot * F::ST, &vmap, 0, 2 * t0, s * 80 + i * 4, full + slot * 8);
        if (++slot == F::NS) { slot = 0; ph ^= 1; }
      }
    }
  } else {
    const int wg = warp >> 2, w = warp & 3;
    for (int s = sfirst; s < s1; s += sstep, par ^= 1) {
      float o[NT == 7 ? 4 : 1][16];
      #pragma unroll
      for (int t = 0; t < (NT == 7 ? 4 : 1); t++)
        #pragma unroll
        for (int i = 0; i < 16; i++) o[t][i] = 0.f;
      mbar_wait(pfull, par);
      int prev = 0;
      #pragma unroll 1
      for (int i = 0; i < 20; i++) {
        if (NT == 7 || (i & 1) == wg) {
          mbar_wait(full + slot * 8, ph);
          const uint64_t dp = i < 16 ? mkdesc(sb + F::P_OFF + i * 2560 + 128, 128, 640, 0) : mkdesc(sb + F::P_OFF + (i - 16) * 10240, 2560, 640, 0);
          const uint32_t pk = i < 16 ? 16 : 320;
          wg_fence();
          if (NT == 7) {
            const uint64_t dv = mkdesc(sb + slot * F::ST + wg * 3072, 7168, 128, 0);
            #pragma unroll
            for (int k = 0; k < 2; k++)
              #pragma unroll
              for (int t = 0; t < 4; t++) if (t > 0 || wg == 0) wg_ss32<0, 0>(o[t], dv + t * 64 + k * 896, dp + k * pk);
          } else {
            const uint64_t dv = mkdesc(sb + slot * F::ST, 1024, 128, 0);
            wg_ss32<0, 0>(o[0], dv, dp); wg_ss32<0, 0>(o[0], dv + 128, dp + pk);
          }
          wg_commit();
          if (NT == 7 && i > 0) { wg_wait<1>(); e_arrive(empty + prev * 8); }
        }
        prev = slot;
        if (++slot == F::NS) { slot = 0; ph ^= 1; }
      }
      wg_wait<0>();
      if (NT == 7) { e_arrive(empty + prev * 8); e_arrive(pempty); }
      #pragma unroll
      for (int t = 0; t < (NT == 7 ? 4 : 1); t++) acc_fence<16>(o[t]);
      if (NT == 1) {
        if (wg == 1) {
          #pragma unroll
          for (int i = 0; i < 4; i++) sts128(sb + 4096 + (i >> 1) * 8192 + (i & 1) * 2048 + (w * 32 + lane) * 16, make_uint4(__float_as_uint(o[0][4 * i]), __float_as_uint(o[0][4 * i + 1]), __float_as_uint(o[0][4 * i + 2]), __float_as_uint(o[0][4 * i + 3])));
        }
      }
      if (NT == 1) {
        bar_sync<1, 256>();
        if (wg == 1) break;
        #pragma unroll
        for (int i = 0; i < 4; i++) { const uint4 u = lds128(sb + 4096 + (i >> 1) * 8192 + (i & 1) * 2048 + (w * 32 + lane) * 16); o[0][4 * i] += __uint_as_float(u.x); o[0][4 * i + 1] += __uint_as_float(u.y); o[0][4 * i + 2] += __uint_as_float(u.z); o[0][4 * i + 3] += __uint_as_float(u.w); }
      }
      const uint32_t st = sb + F::O_OFF + warp * 1536;
      #pragma unroll
      for (int t = 0; t < (NT == 7 ? 4 : 1); t++) {
        if (NT == 7 && t == 0 && wg == 1) continue;
        const uint32_t ao = st + (8 * (lane >> 4) + (lane & 7)) * 48 + (lane & 8) * 2;
        __syncwarp();
        stsm4t(ao, pack_bf(o[t][0], o[t][1]), pack_bf(o[t][2], o[t][3]), pack_bf(o[t][4], o[t][5]), pack_bf(o[t][6], o[t][7]));
        stsm4t(ao + 16 * 48, pack_bf(o[t][8], o[t][9]), pack_bf(o[t][10], o[t][11]), pack_bf(o[t][12], o[t][13]), pack_bf(o[t][14], o[t][15]));
        __syncwarp();
        bf16* dst = out + (size_t)(s * SEG + (lane >> 1)) * OUTW + D + 64 * (NT == 7 ? 3 * wg + t : t0) + 16 * w + 8 * (lane & 1);
        *(uint4*)dst = lds128(st + (lane >> 1) * 48 + (lane & 1) * 16);
        *(uint4*)(dst + 16 * OUTW) = lds128(st + (16 + (lane >> 1)) * 48 + (lane & 1) * 16);
      }
      GT(t0 == 0 && threadIdx.x == 0 && (s & 7) == 7, 208 + (s >> 3));
    }
  }
}

__global__ void __launch_bounds__(256, 1) main_kernel
(const __grid_constant__ CUtensorMap xmap, const __grid_constant__ CUtensorMap xmap2,
    const __grid_constant__ CUtensorMap ymap, const __grid_constant__ CUtensorMap zmap, const bf16* __restrict__ mem0) {
  extern __shared__ __align__(1024) char smem_raw[];
  const uint32_t sb = (smem_u32(smem_raw) + 1023) & ~1023u;
  const int warp = __shfl_sync(0xffffffffu, threadIdx.x >> 5, 0), lane = threadIdx.x & 31;
  const int r = blockIdx.x & 3;
  GT(blockIdx.x == 5 && threadIdx.x == 0, 2);
  if (threadIdx.x == 0) {
    for (int i = 0; i < 15; i++) mbar_init(sb + BAR_OFF + i * 8, (i >= 7 && i < 11) ? 8 : 1);
    asm volatile("fence.mbarrier_init.release.cluster;" ::: "memory");
  }
  if (threadIdx.x < 32) { sts32(sb + ONES_OFF + threadIdx.x * 4, 0x3f803f80u); sts32(sb + ZER_OFF + threadIdx.x * 4, 0); }
  for (int i = threadIdx.x; i < 1280; i += 256) sts32(sb + RX2_OFF + i * 4, 0);
  fence_async_smem();
  __syncthreads();
  cluster_sync_relaxed();
  asm volatile("griddepcontrol.wait;" ::: "memory");
  GT(blockIdx.x == 5 && threadIdx.x == 0, 19);
  asm volatile("griddepcontrol.launch_dependents;");
  uint32_t smid; asm volatile("mov.u32 %0, %%smid;" : "=r"(smid));
  const int myside = tpc_side(min(smid, 155u));
  const int side = rec_side();
  if (r == 0 && threadIdx.x == 0) {
    int role = blockIdx.x >> 2;
    if (SAMESIDE == 1) {
      if (myside == side) { role = atomicAdd(g_side + 156, 1); if (role >= NH) role = NH + atomicAdd(g_side + 157, 1); }
      else { role = NH + atomicAdd(g_side + 157, 1); if (role >= NH + NYCL) role = atomicAdd(g_side + 156, 1); }
    }
    #pragma unroll
    for (int i = 0; i < 4; i++) asm volatile("st.async.weak.shared::cluster.mbarrier::complete_tx::bytes.u32 [%0], %1, [%2];" :: "r"(mapa(sb + BAR_OFF + 120, i)), "r"(role), "r"(mapa(sb + BAR_OFF + 112, i)) : "memory");
  }
  __syncwarp();
  if (warp == 1) e_expect(sb + BAR_OFF + 112, 4);
  mbar_wait(sb + BAR_OFF + 112, 0);
  const int cl = __shfl_sync(0xffffffffu, lds32(sb + BAR_OFF + 120), 0);
  GT(blockIdx.x == 5 && threadIdx.x == 0, 3);
  if (cl < NH) {
    delay_until(clk32() + RWAIT);
    if (warp < 4) {
      asm volatile("pmevent 2;");
      r_score(mem0, sb, cl, r, side, warp, lane);
      GT(cl == 1 && r == 1 && threadIdx.x == 0, 4);
    } else {
      asm volatile("pmevent 3;");
      r_value(&xmap2, &ymap, &zmap, sb, cl, r, side, warp, lane);
    }
    cluster_sync_relaxed();
  } else {
    asm volatile("pmevent 4;");
    h_keys(&xmap, sb, (cl - NH) * 4 + r, r, side, warp, lane);
    GT(cl == NH && r == 0 && threadIdx.x == 0, 5);
    cluster_sync_relaxed();
  }
}
constexpr int A_NEW = 50, A_TILES = (SEQ + A_NEW - 1) / A_NEW, A_NS = 5, A_ST = 12288;
constexpr int AR_OFF = 0, AX_OFF = 2 * A_NS * A_ST, AO_P = 912, AQ_OFF = AX_OFF + 64 * AO_P, AQ_P = 344, AQ_SZ = 64 * AQ_P;
constexpr int AB_OFF = AQ_OFF + 2 * AQ_SZ, A_SMEM = AB_OFF + 256 + 1024;
DEVI void e_tma4d(uint32_t dst, const CUtensorMap* m, int c0, int c1, int c2, int c3, uint32_t bar) {
  asm volatile(ELECT "@pe cp.async.bulk.tensor.4d.shared::cluster.global.mbarrier::complete_tx::bytes [%0], [%1, {%2,%3,%4,%5}], [%6];}" :: "r"(dst), "l"(m), "r"(c0), "r"(c1), "r"(c2), "r"(c3), "r"(bar) : "memory");
}
__global__ void __launch_bounds__(384, 1) parta_kernel(const __grid_constant__ CUtensorMap xmap, const __grid_constant__ CUtensorMap wmap,
                                                       const __grid_constant__ CUtensorMap omap, const char* __restrict__ wqkv, const char* __restrict__ wo, bf16* __restrict__ out) {
  extern __shared__ __align__(1024) char smem_raw[];
  const uint32_t sb = (smem_u32(smem_raw) + 1023) & ~1023u;
  const int warp = __shfl_sync(0xffffffffu, threadIdx.x >> 5, 0), lane = threadIdx.x & 31;
  const int row0 = blockIdx.x * A_NEW - 14;
  const uint32_t xbar = sb + AB_OFF + 160;
  asm volatile("griddepcontrol.launch_dependents;");
  GT(threadIdx.x == 0, 80 + blockIdx.x);
  if (threadIdx.x == 0) {
    for (int i = 0; i < 2 * A_NS; i++) { mbar_init(sb + AB_OFF + i * 16, 1); mbar_init(sb + AB_OFF + i * 16 + 8, 4); }
    mbar_init(xbar, 1);
    asm volatile("fence.mbarrier_init.release.cluster;" ::: "memory");
  }
  __syncthreads();
  if (warp >= 8) {
    asm volatile("setmaxnreg.dec.sync.aligned.u32 24;");
    const int wg = warp & 1;
    if (warp < 10) {
      const uint32_t bars = sb + AB_OFF + wg * A_NS * 16, ring = sb + AR_OFF + wg * A_NS * A_ST;
      int slot = 0, ph = 1;
      #pragma unroll 1
      for (int p = 0; p < 6; p++) {
        #pragma unroll 1
        for (int k = 0; k < D; k += 32) {
          mbar_wait(bars + slot * 16 + 8, ph);
          e_expect(bars + slot * 16, p < 4 ? 12288 : 8192);
          if (p < 4) e_tma4d(ring + slot * A_ST, &wmap, 0, k, 0, 2 * p + wg, bars + slot * 16);
          else e_tma3d(ring + slot * A_ST, &omap, 0, k, 4 * wg + 2 * (p - 4), bars + slot * 16);
          if (++slot == A_NS) { slot = 0; ph ^= 1; }
        }
      }
    } else if (warp == 10) { e_expect(xbar, 57344); e_tma3d(sb + AX_OFF, &xmap, 0, row0, 0, xbar); }
    else {
      const int qd = blockIdx.x & 3;
      if (lane < 14) asm volatile("cp.async.bulk.prefetch.L2.global [%0], 21504;" :: "l"(wqkv + (lane * 4 + qd) * 21504) : "memory");
      else if (lane < 21) asm volatile("cp.async.bulk.prefetch.L2.global [%0], 14336;" :: "l"(wo + ((lane - 14) * 4 + qd) * 14336) : "memory");
    }
  } else {
    asm volatile("setmaxnreg.inc.sync.aligned.u32 240;");
    const int wg = warp >> 2, w = warp & 3, g = lane >> 2, t = lane & 3;
    const uint32_t bars = sb + AB_OFF + wg * A_NS * 16, ring = sb + AR_OFF + wg * A_NS * A_ST, qs = sb + AQ_OFF + wg * AQ_SZ;
    int slot = 0, ph = 0;
    uint32_t a[28][4];
    auto gemm_pass = [&](auto big, float* d) {
      int prev = 0;
      #pragma unroll
      for (int k = 0; k < 14; k++) {
        mbar_wait(bars + slot * 16, ph);
        const uint64_t db = mkdesc(ring + slot * A_ST, 4096, 1024, 1);
        wg_fence();
        if (big.value) { if (k == 0) wg_rs192z<1>(d, a[0], db); else wg_rs192<1>(d, a[2 * k], db); wg_rs192<1>(d, a[2 * k + 1], db + 128); }
        else { if (k == 0) wg_rs128z<1>(d, a[0], db); else wg_rs128<1>(d, a[2 * k], db); wg_rs128<1>(d, a[2 * k + 1], db + 128); }
        wg_commit();
        if (k > 0) { wg_wait<1>(); e_arrive(bars + prev * 16 + 8); }
        prev = slot;
        if (++slot == A_NS) { slot = 0; ph ^= 1; }
      }
      wg_wait<0>();
      e_arrive(bars + prev * 16 + 8);
    };
    mbar_wait(xbar, 0);
    {
      const int rr = 16 * w + (lane & 15);
      #pragma unroll
      for (int ks = 0; ks < 28; ks++)
        ldsm4(sb + AX_OFF + (ks >> 2) * 8192 + rr * 128 + ((((ks & 3) * 2 + (lane >> 4)) ^ (rr & 7)) << 4), a[ks][0], a[ks][1], a[ks][2], a[ks][3]);
    }
    bar_sync<1, 256>();
    if (wg == 1) bar_sync<4, 256>();
    #pragma unroll 1
    for (int p = 0; p < 4; p++) {
      {
        float d[96];
        gemm_pass(std::true_type(), d);
        acc_fence<96>(d);
        if (p == 0 && wg == 0) bar_arrive<4, 256>();
        bar_sync_id(2 + wg, 128);
        const uint32_t q = qs + (16 * w + g) * AQ_P + 4 * t;
        #pragma unroll
        for (int nb = 0; nb < 24; nb++) if ((nb & 7) < 7) {
          const int o = (nb >> 3) * 112 + (nb & 7) * 16;
          sts32(q + o, pack_bf(d[4 * nb], d[4 * nb + 1])); sts32(q + 8 * AQ_P + o, pack_bf(d[4 * nb + 2], d[4 * nb + 3]));
        }
      }
      bar_sync_id(2 + wg, 128);
      if (lane < 25) {
        const int ra = 14 + 25 * (w & 1) + lane;
        const uint32_t qb = qs + (w >> 1) * 56 + ra * AQ_P;
        float sc[8];
        {
          float qa[28];
          #pragma unroll
          for (int i = 0; i < 7; i++) { const uint2 u = lds64(qb + i * 8); qa[4 * i] = bf_lo(u.x); qa[4 * i + 1] = bf_hi(u.x); qa[4 * i + 2] = bf_lo(u.y); qa[4 * i + 3] = bf_hi(u.y); }
          #pragma unroll
          for (int n = 0; n < 8; n++) {
            float x0 = 0, x1 = 0;
            #pragma unroll
            for (int i = 0; i < 7; i++) {
              const uint2 u = lds64(qb + 112 - 2 * n * AQ_P + i * 8);
              x0 = fmaf(qa[4 * i], bf_lo(u.x), x0); x1 = fmaf(qa[4 * i + 1], bf_hi(u.x), x1); x0 = fmaf(qa[4 * i + 2], bf_lo(u.y), x0); x1 = fmaf(qa[4 * i + 3], bf_hi(u.y), x1);
            }
            sc[n] = row0 + ra - 2 * n >= 0 ? x0 + x1 : -INFINITY;
          }
        }
        const float scl = 0.18898223650461361f * 1.4426950408889634f;
        float mx = sc[0], den = 0;
        #pragma unroll
        for (int n = 1; n < 8; n++) mx = fmaxf(mx, sc[n]);
        #pragma unroll
        for (int n = 0; n < 8; n++) { sc[n] = ex2((sc[n] - mx) * scl); den += sc[n]; }
        den = rcpf(den);
        const uint32_t ob = sb + AX_OFF + ra * AO_P + (4 * p + 2 * wg + (w >> 1)) * 56;
        #pragma unroll
        for (int i = 0; i < 7; i++) {
          float o0 = 0, o1 = 0, o2 = 0, o3 = 0;
          #pragma unroll
          for (int n = 0; n < 8; n++) {
            const uint2 u = lds64(qb + 224 - 2 * n * AQ_P + i * 8);
            o0 = fmaf(sc[n], bf_lo(u.x), o0); o1 = fmaf(sc[n], bf_hi(u.x), o1); o2 = fmaf(sc[n], bf_lo(u.y), o2); o3 = fmaf(sc[n], bf_hi(u.y), o3);
          }
          sts64(ob + i * 8, pack_bf(o0 * den, o1 * den), pack_bf(o2 * den, o3 * den));
        }
      }
      __syncwarp();
    }
    bar_sync<1, 256>();
    {
      const uint32_t ro = sb + AX_OFF + (16 * w + (lane & 15)) * AO_P + (lane >> 4) * 16;
      #pragma unroll
      for (int ks = 0; ks < 28; ks++) ldsm4(ro + ks * 32, a[ks][0], a[ks][1], a[ks][2], a[ks][3]);
      #pragma unroll 1
      for (int m = 0; m < 2; m++) {
        float d[64];
        gemm_pass(std::false_type(), d);
        acc_fence<64>(d);
        const uint32_t st = qs + w * 3840;
        __syncwarp();
        #pragma unroll
        for (int k = 0; k < 7; k++) {
          const int n0 = 2 * k + (2 * k >= 7), n1 = 2 * k + 1 + (2 * k + 1 >= 7);
          stsm4(st + (lane & 15) * 240 + (lane >> 4) * 16 + k * 32, pack_bf(d[4 * n0], d[4 * n0 + 1]), pack_bf(d[4 * n0 + 2], d[4 * n0 + 3]), pack_bf(d[4 * n1], d[4 * n1 + 1]), pack_bf(d[4 * n1 + 2], d[4 * n1 + 3]));
        }
        __syncwarp();
        #pragma unroll
        for (int i = 0; i < 7; i++) {
          const int id = i * 32 + lane, rr = id / 14, c = id % 14, tr = 16 * w + rr;
          const uint4 v = lds128(st + rr * 240 + c * 16);
          if (tr >= 14 && row0 + tr < SEQ) *(uint4*)(out + (size_t)(row0 + tr) * OUTW + wg * 224 + m * 112 + c * 8) = v;
        }
      }
    }
    GT(threadIdx.x == 0, 130 + blockIdx.x);
  }
}
#define NFIN 7
#define NTAIL 5
typedef CUresult (*EncodeFn)(CUtensorMap*, CUtensorMapDataType, cuuint32_t, void*, const cuuint64_t*, const cuuint64_t*, const cuuint32_t*, const cuuint32_t*,
                             CUtensorMapInterleave, CUtensorMapSwizzle, CUtensorMapL2promotion, CUtensorMapFloatOOBfill);
static void make_map(EncodeFn enc, CUtensorMap* m, const void* p, int rank, cuuint64_t d0, cuuint64_t d1, cuuint64_t d2, cuuint64_t s1, cuuint64_t s2,
                     cuuint32_t b0, cuuint32_t b1, cuuint32_t b2, bool swz, cuuint64_t d3 = 1, cuuint64_t s3 = 0) {
  cuuint64_t gd[4] = {d0, d1, d2, d3}, gs[3] = {s1, s2, s3}; cuuint32_t bx[4] = {b0, b1, b2, 1}, es[4] = {1, 1, 1, 1};
  enc(m, CU_TENSOR_MAP_DATA_TYPE_BFLOAT16, rank, (void*)p, gd, gs, bx, es, CU_TENSOR_MAP_INTERLEAVE_NONE,
      swz ? CU_TENSOR_MAP_SWIZZLE_128B : CU_TENSOR_MAP_SWIZZLE_NONE, CU_TENSOR_MAP_L2_PROMOTION_L2_128B, CU_TENSOR_MAP_FLOAT_OOB_FILL_NONE);
}

extern "C" void kernel_launch(void* const* d_in, const int* in_sizes, int n_in, void* d_out, int out_size) {
  static EncodeFn enc = nullptr;
  static void *kt = nullptr, *yt = nullptr;
  cudaLaunchAttribute at[2];
  at[0].id = cudaLaunchAttributeProgrammaticStreamSerialization; at[0].val.programmaticStreamSerializationAllowed = 1;
  at[1].id = cudaLaunchAttributeClusterDimension; at[1].val.clusterDim.x = 4; at[1].val.clusterDim.y = 1; at[1].val.clusterDim.z = 1;
  if (!enc) {
    void* fn = nullptr; cudaDriverEntryPointQueryResult qr;
    cudaGetDriverEntryPoint("cuTensorMapEncodeTiled", &fn, cudaEnableDefault, &qr);
    enc = (EncodeFn)fn;
    cudaFuncSetAttribute(prep_kernel, cudaFuncAttributeMaxDynamicSharedMemorySize, PREP_SMEM);
    cudaFuncSetAttribute(main_kernel, cudaFuncAttributeMaxDynamicSharedMemorySize, MAIN_SMEM);
    cudaFuncSetAttribute(parta_kernel, cudaFuncAttributeMaxDynamicSharedMemorySize, A_SMEM);
    cudaFuncSetAttribute(finish_kernel<7>, cudaFuncAttributeMaxDynamicSharedMemorySize, Fin<7>::SMEM);
    cudaFuncSetAttribute(finish_kernel<1>, cudaFuncAttributeMaxDynamicSharedMemorySize, Fin<1>::SMEM);
    cudaGetSymbolAddress(&kt, g_vt);
    cudaGetSymbolAddress(&yt, g_yt);
  }
  CUtensorMap ax, aw, ao, bx, mq, mk, mv, mo, mz, mvt, my, bx2;
  make_map(enc, &ax, d_in[0], 3, 64, SEQ, 7, 896, 128, 64, 64, 7, true);
  make_map(enc, &aw, d_in[1], 4, 56, D, 3, 2688, 896, 64, 32, 3, true, 8, 112);
  make_map(enc, &ao, d_in[2], 3, 56, D, 8, 896, 112, 64, 32, 2, true);
  make_map(enc, &bx, d_in[3], 3, 64, SEQ, 7, 896, 128, 64, 8, 7, true);
  make_map(enc, &mq, d_in[5], 3, 64, D, 64, 8192, 128, 64, 64, 4, true);
  make_map(enc, &mk, d_in[6], 3, 64, D, 64, 8192, 128, 64, SL, 4, true);
  make_map(enc, &mv, d_in[7], 3, 64, D, 64, 8192, 128, 64, SL, 4, true);
  make_map(enc, &mo, d_in[8], 2, D, 4096, 1, 896, 0, 64, 256, 1, true);
  make_map(enc, &mz, kt, 3, 224, 16, NSEG * 80, 448, 7168, 224, 4, 4, false);
  make_map(enc, &mvt, kt, 3, 256, 14, NSEG * 80, 512, 7168, 256, 2, 4, false);
  make_map(enc, &my, yt, 3, 224, 16, NSEG * 64, 448, 7168, 224, 4, 4, false);
  make_map(enc, &bx2, d_in[3], 2, D, SEQ, 1, 896, 0, 64, 32, 1, true);
  cudaLaunchConfig_t c = {};
  c.stream = cudaStreamPerThread;
  c.gridDim = dim3(132); c.blockDim = dim3(320); c.dynamicSmemBytes = PREP_SMEM; c.attrs = at; c.numAttrs = 0;
  cudaLaunchKernelEx(&c, prep_kernel, mq, mk, mv, mo);
  c.gridDim = dim3((NH + NYCL) * 4); c.blockDim = dim3(256); c.dynamicSmemBytes = MAIN_SMEM; c.numAttrs = 2;
  cudaLaunchKernelEx(&c, main_kernel, bx, bx2, my, mz, (const bf16*)d_in[4]);
  c.numAttrs = 1;
  c.gridDim = dim3(NFIN); c.blockDim = dim3(288); c.dynamicSmemBytes = Fin<7>::SMEM;
  cudaLaunchKernelEx(&c, finish_kernel<7>, mvt, (bf16*)d_out, 0, NSEG - NTAIL);
  c.gridDim = dim3(A_TILES); c.blockDim = dim3(384); c.dynamicSmemBytes = A_SMEM;
  cudaLaunchKernelEx(&c, parta_kernel, ax, aw, ao, (const char*)d_in[1], (const char*)d_in[2], (bf16*)d_out);
  c.gridDim = dim3(7 * NTAIL); c.blockDim = dim3(288); c.dynamicSmemBytes = Fin<1>::SMEM;
  cudaLaunchKernelEx(&c, finish_kernel<1>, mvt, (bf16*)d_out, NSEG - NTAIL, NSEG);
}
```

```cpp
#include <cuda_runtime.h>
#include <cuda_bf16.h>
#include <cuda.h>
#include <stdint.h>
#include <type_traits>
#define DEVI __device__ __forceinline__
typedef __nv_bfloat16 bf16;

DEVI uint32_t smem_u32(const void* p) { return (uint32_t)__cvta_generic_to_shared(p); }
DEVI uint32_t mapa(uint32_t a, uint32_t r) { uint32_t o; asm("mapa.shared::cluster.u32 %0, %1, %2;" : "=r"(o) : "r"(a), "r"(r)); return o; }
DEVI unsigned clk32() { unsigned c; asm volatile("mov.u32 %0, %%clock;" : "=r"(c) :: "memory"); return c; }
DEVI void mbar_init(uint32_t bar, uint32_t n) { asm volatile("mbarrier.init.shared::cta.b64 [%0], %1;" :: "r"(bar), "r"(n) : "memory"); }
DEVI void mbar_arrive(uint32_t bar) { asm volatile("mbarrier.arrive.shared::cta.b64 _, [%0];" :: "r"(bar) : "memory"); }
DEVI void mbar_arrive_remote(uint32_t bar) { asm volatile("mbarrier.arrive.relaxed.cluster.shared::cluster.b64 _, [%0];" :: "r"(bar) : "memory"); }
#define SPIN_LIMIT 2000000
DEVI void mbar_wait(uint32_t bar, uint32_t par) {
  asm volatile("{\n.reg .pred p;\n.reg .u32 c;\nmbarrier.try_wait.parity.shared::cta.b64 p, [%0], %1;\n@p bra LD;\nmov.u32 c, 0;\nLW:\n"
               "mbarrier.try_wait.parity.shared::cta.b64 p, [%0], %1;\n@p bra LD;\nadd.u32 c, c, 1;\nsetp.lt.u32 p, c, 400000;\n@p bra LW;\ntrap;\nLD:\n}" :: "r"(bar), "r"(par) : "memory");
}
DEVI bool mbar_test(uint32_t bar, uint32_t par) {
  uint32_t ok; asm volatile("{.reg .pred p; mbarrier.test_wait.parity.shared::cta.b64 p, [%1], %2; selp.u32 %0, 1, 0, p;}" : "=r"(ok) : "r"(bar), "r"(par) : "memory");
  return __all_sync(0xffffffffu, ok);
}
template <int ID, int N> DEVI void bar_sync() { asm volatile("bar.sync %0, %1;" :: "n"(ID), "n"(N) : "memory"); }
template <int ID, int N> DEVI void bar_arrive() { asm volatile("bar.arrive %0, %1;" :: "n"(ID), "n"(N) : "memory"); }
DEVI void bar_sync_id(int id, int n) { asm volatile("bar.sync %0, %1;" :: "r"(id), "r"(n) : "memory"); }
DEVI void bar_arrive_id(int id, int n) { asm volatile("bar.arrive %0, %1;" :: "r"(id), "r"(n) : "memory"); }
DEVI void sched_fence() { asm volatile("pmevent 0;"); }
DEVI void st_async32(uint32_t a, uint32_t v, uint32_t bar) { asm volatile("st.async.weak.shared::cluster.mbarrier::complete_tx::bytes.u32 [%0], %1, [%2];" :: "r"(a), "r"(v), "r"(bar) : "memory"); }
DEVI void fence_async_smem() { asm volatile("fence.proxy.async.shared::cta;" ::: "memory"); }
DEVI void fence_async_global() { asm volatile("fence.proxy.async.global;" ::: "memory"); }
DEVI void mma16816(float* c, uint32_t a0, uint32_t a1, uint32_t a2, uint32_t a3, uint32_t b0, uint32_t b1) {
  asm volatile("mma.sync.aligned.m16n8k16.row.col.f32.bf16.bf16.f32 {%0,%1,%2,%3}, {%4,%5,%6,%7}, {%8,%9}, {%0,%1,%2,%3};"
    : "+f"(c[0]), "+f"(c[1]), "+f"(c[2]), "+f"(c[3]) : "r"(a0), "r"(a1), "r"(a2), "r"(a3), "r"(b0), "r"(b1));
}
DEVI void mma16816z(float* c, uint32_t a0, uint32_t a1, uint32_t a2, uint32_t a3, uint32_t b0, uint32_t b1) {
  asm volatile("mma.sync.aligned.m16n8k16.row.col.f32.bf16.bf16.f32 {%0,%1,%2,%3}, {%4,%5,%6,%7}, {%8,%9}, {%10,%10,%10,%10};"
    : "=f"(c[0]), "=f"(c[1]), "=f"(c[2]), "=f"(c[3]) : "r"(a0), "r"(a1), "r"(a2), "r"(a3), "r"(b0), "r"(b1), "f"(0.f));
}
DEVI void mma1688(float* c, uint32_t a0, uint32_t a1, uint32_t b0) {
  asm volatile("mma.sync.aligned.m16n8k8.row.col.f32.bf16.bf16.f32 {%0,%1,%2,%3}, {%4,%5}, {%6}, {%0,%1,%2,%3};"
    : "+f"(c[0]), "+f"(c[1]), "+f"(c[2]), "+f"(c[3]) : "r"(a0), "r"(a1), "r"(b0));
}
DEVI void ldsm4(uint32_t a, uint32_t& r0, uint32_t& r1, uint32_t& r2, uint32_t& r3) { asm volatile("ldmatrix.sync.aligned.m8n8.x4.shared.b16 {%0,%1,%2,%3}, [%4];" : "=r"(r0), "=r"(r1), "=r"(r2), "=r"(r3) : "r"(a) : "memory"); }
DEVI void ldsm2(uint32_t a, uint32_t& r0, uint32_t& r1) { asm volatile("ldmatrix.sync.aligned.m8n8.x2.shared.b16 {%0,%1}, [%2];" : "=r"(r0), "=r"(r1) : "r"(a) : "memory"); }
DEVI void ldsm4t(uint32_t a, uint32_t& r0, uint32_t& r1, uint32_t& r2, uint32_t& r3) { asm volatile("ldmatrix.sync.aligned.m8n8.x4.trans.shared.b16 {%0,%1,%2,%3}, [%4];" : "=r"(r0), "=r"(r1), "=r"(r2), "=r"(r3) : "r"(a) : "memory"); }
DEVI void ldsm2t(uint32_t a, uint32_t& r0, uint32_t& r1) { asm volatile("ldmatrix.sync.aligned.m8n8.x2.trans.shared.b16 {%0,%1}, [%2];" : "=r"(r0), "=r"(r1) : "r"(a) : "memory"); }
DEVI void stsm4(uint32_t a, uint32_t r0, uint32_t r1, uint32_t r2, uint32_t r3) { asm volatile("stmatrix.sync.aligned.m8n8.x4.shared.b16 [%0], {%1,%2,%3,%4};" :: "r"(a), "r"(r0), "r"(r1), "r"(r2), "r"(r3) : "memory"); }
DEVI void stsm2(uint32_t a, uint32_t r0, uint32_t r1) { asm volatile("stmatrix.sync.aligned.m8n8.x2.shared.b16 [%0], {%1,%2};" :: "r"(a), "r"(r0), "r"(r1) : "memory"); }
DEVI void stsm4t(uint32_t a, uint32_t r0, uint32_t r1, uint32_t r2, uint32_t r3) { asm volatile("stmatrix.sync.aligned.m8n8.x4.trans.shared.b16 [%0], {%1,%2,%3,%4};" :: "r"(a), "r"(r0), "r"(r1), "r"(r2), "r"(r3) : "memory"); }
DEVI uint32_t movm(uint32_t a) { uint32_t d; asm volatile("movmatrix.sync.aligned.m8n8.trans.b16 %0, %1;" : "=r"(d) : "r"(a)); return d; }
DEVI uint32_t pack_bf(float lo, float hi) { uint32_t d; asm("cvt.rn.bf16x2.f32 %0, %1, %2;" : "=r"(d) : "f"(hi), "f"(lo)); return d; }
DEVI float bf_lo(uint32_t v) { return __uint_as_float(v << 16); }
DEVI float bf_hi(uint32_t v) { return __uint_as_float(v & 0xffff0000u); }
DEVI float ex2(float x) { float y; asm("ex2.approx.ftz.f32 %0, %1;" : "=f"(y) : "f"(x)); return y; }
DEVI float rcpf(float x) { float y; asm("rcp.approx.ftz.f32 %0, %1;" : "=f"(y) : "f"(x)); return y; }
DEVI uint4 lds128(uint32_t a) { uint4 v; asm volatile("ld.shared.v4.u32 {%0,%1,%2,%3}, [%4];" : "=r"(v.x), "=r"(v.y), "=r"(v.z), "=r"(v.w) : "r"(a) : "memory"); return v; }
DEVI uint2 lds64(uint32_t a) { uint2 v; asm volatile("ld.shared.v2.u32 {%0,%1}, [%2];" : "=r"(v.x), "=r"(v.y) : "r"(a) : "memory"); return v; }
DEVI uint32_t lds32(uint32_t a) { uint32_t v; asm volatile("ld.shared.u32 %0, [%1];" : "=r"(v) : "r"(a) : "memory"); return v; }
DEVI void sts32(uint32_t a, uint32_t v) { asm volatile("st.shared.u32 [%0], %1;" :: "r"(a), "r"(v) : "memory"); }
DEVI void sts64(uint32_t a, uint32_t x, uint32_t y) { asm volatile("st.shared.v2.u32 [%0], {%1,%2};" :: "r"(a), "r"(x), "r"(y) : "memory"); }
DEVI void sts64f(uint32_t a, float x, float y) { asm volatile("st.shared.v2.f32 [%0], {%1,%2};" :: "r"(a), "f"(x), "f"(y) : "memory"); }
DEVI void sts128(uint32_t a, uint4 v) { asm volatile("st.shared.v4.u32 [%0], {%1,%2,%3,%4};" :: "r"(a), "r"(v.x), "r"(v.y), "r"(v.z), "r"(v.w) : "memory"); }
DEVI uint4 ldg128_relaxed(const void* p) { uint4 v; asm volatile("{.reg .b128 t; ld.relaxed.gpu.global.b128 t, [%2]; mov.b128 {%0,%1}, t;}" : "=l"(*(unsigned long long*)&v.x), "=l"(*(unsigned long long*)&v.z) : "l"(p) : "memory"); return v; }
DEVI unsigned ldg_relaxed(const unsigned* p) { unsigned v; asm volatile("ld.relaxed.gpu.global.u32 %0, [%1];" : "=r"(v) : "l"(p) : "memory"); return v; }
template <int NS = 200> DEVI void wait_flag(const unsigned* p, unsigned target) { int spin = 0; while (__any_sync(0xffffffffu, ldg_relaxed(p) < target)) { if (NS) __nanosleep(NS); if (++spin > SPIN_LIMIT) __trap(); } }
template <int N> DEVI void bulk_wait() { asm volatile("cp.async.bulk.wait_group %0;" :: "n"(N) : "memory"); }
#define ELECT "{.reg .pred pe; elect.sync _|pe, 0xffffffff;\n"
DEVI void e_expect(uint32_t bar, uint32_t tx) { asm volatile(ELECT "@pe mbarrier.arrive.expect_tx.shared::cta.b64 _, [%0], %1;}" :: "r"(bar), "r"(tx) : "memory"); }
DEVI void e_arrive(uint32_t bar) { asm volatile(ELECT "@pe mbarrier.arrive.shared::cta.b64 _, [%0];}" :: "r"(bar) : "memory"); }
DEVI void e_g2s(uint32_t dst, const void* src, uint32_t bytes, uint32_t bar) { asm volatile(ELECT "@pe cp.async.bulk.shared::cluster.global.mbarrier::complete_tx::bytes [%0], [%1], %2, [%3];}" :: "r"(dst), "l"(src), "r"(bytes), "r"(bar) : "memory"); }
DEVI void e_s2c(uint32_t dst, uint32_t src, uint32_t bytes, uint32_t bar) { asm volatile(ELECT "@pe cp.async.bulk.shared::cluster.shared::cta.mbarrier::complete_tx::bytes [%0], [%1], %2, [%3];}" :: "r"(dst), "r"(src), "r"(bytes), "r"(bar) : "memory"); }
DEVI void e_s2g(void* dst, uint32_t src, uint32_t bytes) { asm volatile(ELECT "@pe cp.async.bulk.global.shared::cta.bulk_group [%0], [%1], %2;}" :: "l"(dst), "r"(src), "r"(bytes) : "memory"); }
DEVI void bulk_commit() { asm volatile("cp.async.bulk.commit_group;" ::: "memory"); }
DEVI void e_tma3d_mc(uint32_t dst, const CUtensorMap* m, int c0, int c1, int c2, uint32_t bar, uint16_t mask) {
  asm volatile(ELECT "@pe cp.async.bulk.tensor.3d.shared::cluster.global.mbarrier::complete_tx::bytes.multicast::cluster [%0], [%1, {%2,%3,%4}], [%5], %6;}" :: "r"(dst), "l"(m), "r"(c0), "r"(c1), "r"(c2), "r"(bar), "h"(mask) : "memory");
}
DEVI void e_tma3d(uint32_t dst, const CUtensorMap* m, int c0, int c1, int c2, uint32_t bar) {
  asm volatile(ELECT "@pe cp.async.bulk.tensor.3d.shared::cluster.global.mbarrier::complete_tx::bytes [%0], [%1, {%2,%3,%4}], [%5];}" :: "r"(dst), "l"(m), "r"(c0), "r"(c1), "r"(c2), "r"(bar) : "memory");
}
DEVI void e_tma2d(uint32_t dst, const CUtensorMap* m, int c0, int c1, uint32_t bar) {
  asm volatile(ELECT "@pe cp.async.bulk.tensor.2d.shared::cluster.global.mbarrier::complete_tx::bytes [%0], [%1, {%2,%3}], [%4];}" :: "r"(dst), "l"(m), "r"(c0), "r"(c1), "r"(bar) : "memory");
}
DEVI void red_add_if(bool c, unsigned* p, unsigned v) { asm volatile("{.reg .pred p; setp.ne.s32 p, %2, 0; @p red.relaxed.gpu.global.add.u32 [%0], %1;}" :: "l"(p), "r"(v), "r"((int)c) : "memory"); }
DEVI void wg_fence() { asm volatile("wgmma.fence.sync.aligned;" ::: "memory"); }
DEVI void wg_commit() { asm volatile("wgmma.commit_group.sync.aligned;" ::: "memory"); }
template <int N> DEVI void wg_wait() { asm volatile("wgmma.wait_group.sync.aligned %0;" :: "n"(N) : "memory"); }
template <int N> DEVI void acc_fence(float* d) {
  #pragma unroll
  for (int i = 0; i < N; i++) asm volatile("" : "+f"(d[i]) :: "memory");
}
DEVI void cluster_sync_full() { asm volatile("barrier.cluster.arrive.aligned; barrier.cluster.wait.aligned;" ::: "memory"); }
DEVI void cluster_sync_relaxed() { asm volatile("barrier.cluster.arrive.relaxed.aligned; barrier.cluster.wait.aligned;" ::: "memory"); }
DEVI uint64_t mkdesc(uint32_t addr, uint32_t lbo, uint32_t sbo, uint32_t swz) {
  return (uint64_t)((addr & 0x3FFFF) >> 4) | ((uint64_t)(lbo >> 4) << 16) | ((uint64_t)(sbo >> 4) << 32) | ((uint64_t)swz << 62);
}
#define OPAQUE(x) asm volatile("" : "+r"(x))

constexpr int D = 448, NH = 16, SL = 112, SEG = 32, NSEG = 64, SEQ = 2048, OUTW = 896;
__device__ uint4 g_frag[2][NH * 28 * 28 * 32];
constexpr int PL = D * 8;
__device__ __align__(1024) bf16 g_yt[(size_t)NSEG * 64 * PL];
__device__ __align__(1024) bf16 g_vt[(size_t)NSEG * 80 * PL];
__device__ __align__(1024) bf16 g_p[(size_t)NSEG * 80 * 256];
__device__ __align__(1024) uint4 g_aw[D * 224];
__device__ __align__(1024) char g_accraw[2 * 262144];
__device__ __align__(8) int g_side[160];
DEVI char* acc_base() { return (char*)(((uintptr_t)g_accraw + 262143) & ~(uintptr_t)262143); }
DEVI uint32_t acc_off(int s, int q, int side) {
  const int pair = ((s >> 1) & 3) * 4 + q;
  return (pair * 2 + ((side ^ pair ^ (pair >> 3)) & 1)) * 4096 + (s & 1) * 128;
}
DEVI unsigned* tflag_ptr(int side) { return (unsigned*)(acc_base() + (32 + side) * 4096); }
DEVI unsigned* vflag_ptr(int side) { return (unsigned*)(acc_base() + (36 + side) * 4096); }
constexpr unsigned VFLAG_N = 128, TFLAG_N = 14;
constexpr uint32_t CNT = 0x41800000u;
#define NFIN 6
#define NTAIL 6
DEVI int tpc_side(int sm) { const int2 d = __ldcg((const int2*)(g_side + (sm & ~1))); return d.x + d.y > 0; }
DEVI int rec_side() { return __shfl_sync(0xffffffffu, tpc_side(0) ^ 1, 0); }
DEVI void delay_until(unsigned tend) { long long c; do { c = clock64(); } while ((int)((unsigned)c - tend) < 0); }
#define GT(c, i)
#define GTL(c, i) GT(c, i)
template <int TB> DEVI void wg_rs64(float* d, const uint32_t* a, uint64_t db) {
  asm volatile("wgmma.mma_async.sync.aligned.m64n64k16.f32.bf16.bf16 {%0,%1,%2,%3,%4,%5,%6,%7,%8,%9,%10,%11,%12,%13,%14,%15,%16,%17,%18,%19,%20,%21,%22,%23,%24,%25,%26,%27,%28,%29,%30,%31}, {%32,%33,%34,%35}, %36, 1, 1, 1, %37;"
    : "+f"(d[0]), "+f"(d[1]), "+f"(d[2]), "+f"(d[3]), "+f"(d[4]), "+f"(d[5]), "+f"(d[6]), "+f"(d[7]), "+f"(d[8]), "+f"(d[9]), "+f"(d[10]), "+f"(d[11]), "+f"(d[12]), "+f"(d[13]), "+f"(d[14]), "+f"(d[15]), "+f"(d[16]), "+f"(d[17]), "+f"(d[18]), "+f"(d[19]), "+f"(d[20]), "+f"(d[21]), "+f"(d[22]), "+f"(d[23]), "+f"(d[24]), "+f"(d[25]), "+f"(d[26]), "+f"(d[27]), "+f"(d[28]), "+f"(d[29]), "+f"(d[30]), "+f"(d[31])
    : "r"(a[0]), "r"(a[1]), "r"(a[2]), "r"(a[3]), "l"(db), "n"(TB));
}
template <int TB> DEVI void wg_rs64z(float* d, const uint32_t* a, uint64_t db) {
  asm volatile("wgmma.mma_async.sync.aligned.m64n64k16.f32.bf16.bf16 {%0,%1,%2,%3,%4,%5,%6,%7,%8,%9,%10,%11,%12,%13,%14,%15,%16,%17,%18,%19,%20,%21,%22,%23,%24,%25,%26,%27,%28,%29,%30,%31}, {%32,%33,%34,%35}, %36, 0, 1, 1, %37;"
    : "=f"(d[0]), "=f"(d[1]), "=f"(d[2]), "=f"(d[3]), "=f"(d[4]), "=f"(d[5]), "=f"(d[6]), "=f"(d[7]), "=f"(d[8]), "=f"(d[9]), "=f"(d[10]), "=f"(d[11]), "=f"(d[12]), "=f"(d[13]), "=f"(d[14]), "=f"(d[15]), "=f"(d[16]), "=f"(d[17]), "=f"(d[18]), "=f"(d[19]), "=f"(d[20]), "=f"(d[21]), "=f"(d[22]), "=f"(d[23]), "=f"(d[24]), "=f"(d[25]), "=f"(d[26]), "=f"(d[27]), "=f"(d[28]), "=f"(d[29]), "=f"(d[30]), "=f"(d[31])
    : "r"(a[0]), "r"(a[1]), "r"(a[2]), "r"(a[3]), "l"(db), "n"(TB));
}
template <int TA, int TB> DEVI void wg_ss32(float* d, uint64_t da, uint64_t db) {
  asm volatile("wgmma.mma_async.sync.aligned.m64n32k16.f32.bf16.bf16 {%0,%1,%2,%3,%4,%5,%6,%7,%8,%9,%10,%11,%12,%13,%14,%15}, %16, %17, 1, 1, 1, %18, %19;"
    : "+f"(d[0]), "+f"(d[1]), "+f"(d[2]), "+f"(d[3]), "+f"(d[4]), "+f"(d[5]), "+f"(d[6]), "+f"(d[7]), "+f"(d[8]), "+f"(d[9]), "+f"(d[10]), "+f"(d[11]), "+f"(d[12]), "+f"(d[13]), "+f"(d[14]), "+f"(d[15])
    : "l"(da), "l"(db), "n"(TA), "n"(TB));
}
template <int TA, int TB> DEVI void wg_ss32z(float* d, uint64_t da, uint64_t db) {
  asm volatile("wgmma.mma_async.sync.aligned.m64n32k16.f32.bf16.bf16 {%0,%1,%2,%3,%4,%5,%6,%7,%8,%9,%10,%11,%12,%13,%14,%15}, %16, %17, 0, 1, 1, %18, %19;"
    : "=f"(d[0]), "=f"(d[1]), "=f"(d[2]), "=f"(d[3]), "=f"(d[4]), "=f"(d[5]), "=f"(d[6]), "=f"(d[7]), "=f"(d[8]), "=f"(d[9]), "=f"(d[10]), "=f"(d[11]), "=f"(d[12]), "=f"(d[13]), "=f"(d[14]), "=f"(d[15])
    : "l"(da), "l"(db), "n"(TA), "n"(TB));
}
template <int TA, int TB> DEVI void wg_ss112(float* d, uint64_t da, uint64_t db) {
  asm volatile("wgmma.mma_async.sync.aligned.m64n112k16.f32.bf16.bf16 {%0,%1,%2,%3,%4,%5,%6,%7,%8,%9,%10,%11,%12,%13,%14,%15,%16,%17,%18,%19,%20,%21,%22,%23,%24,%25,%26,%27,%28,%29,%30,%31,%32,%33,%34,%35,%36,%37,%38,%39,%40,%41,%42,%43,%44,%45,%46,%47,%48,%49,%50,%51,%52,%53,%54,%55}, %56, %57, 1, 1, 1, %58, %59;"
    : "+f"(d[0]), "+f"(d[1]), "+f"(d[2]), "+f"(d[3]), "+f"(d[4]), "+f"(d[5]), "+f"(d[6]), "+f"(d[7]), "+f"(d[8]), "+f"(d[9]), "+f"(d[10]), "+f"(d[11]), "+f"(d[12]), "+f"(d[13]), "+f"(d[14]), "+f"(d[15]), "+f"(d[16]), "+f"(d[17]), "+f"(d[18]), "+f"(d[19]), "+f"(d[20]), "+f"(d[21]), "+f"(d[22]), "+f"(d[23]), "+f"(d[24]), "+f"(d[25]), "+f"(d[26]), "+f"(d[27]), "+f"(d[28]), "+f"(d[29]), "+f"(d[30]), "+f"(d[31]), "+f"(d[32]), "+f"(d[33]), "+f"(d[34]), "+f"(d[35]), "+f"(d[36]), "+f"(d[37]), "+f"(d[38]), "+f"(d[39]), "+f"(d[40]), "+f"(d[41]), "+f"(d[42]), "+f"(d[43]), "+f"(d[44]), "+f"(d[45]), "+f"(d[46]), "+f"(d[47]), "+f"(d[48]), "+f"(d[49]), "+f"(d[50]), "+f"(d[51]), "+f"(d[52]), "+f"(d[53]), "+f"(d[54]), "+f"(d[55])
    : "l"(da), "l"(db), "n"(TA), "n"(TB));
}
template <int TA, int TB> DEVI void wg_ss112z(float* d, uint64_t da, uint64_t db) {
  asm volatile("wgmma.mma_async.sync.aligned.m64n112k16.f32.bf16.bf16 {%0,%1,%2,%3,%4,%5,%6,%7,%8,%9,%10,%11,%12,%13,%14,%15,%16,%17,%18,%19,%20,%21,%22,%23,%24,%25,%26,%27,%28,%29,%30,%31,%32,%33,%34,%35,%36,%37,%38,%39,%40,%41,%42,%43,%44,%45,%46,%47,%48,%49,%50,%51,%52,%53,%54,%55}, %56, %57, 0, 1, 1, %58, %59;"
    : "=f"(d[0]), "=f"(d[1]), "=f"(d[2]), "=f"(d[3]), "=f"(d[4]), "=f"(d[5]), "=f"(d[6]), "=f"(d[7]), "=f"(d[8]), "=f"(d[9]), "=f"(d[10]), "=f"(d[11]), "=f"(d[12]), "=f"(d[13]), "=f"(d[14]), "=f"(d[15]), "=f"(d[16]), "=f"(d[17]), "=f"(d[18]), "=f"(d[19]), "=f"(d[20]), "=f"(d[21]), "=f"(d[22]), "=f"(d[23]), "=f"(d[24]), "=f"(d[25]), "=f"(d[26]), "=f"(d[27]), "=f"(d[28]), "=f"(d[29]), "=f"(d[30]), "=f"(d[31]), "=f"(d[32]), "=f"(d[33]), "=f"(d[34]), "=f"(d[35]), "=f"(d[36]), "=f"(d[37]), "=f"(d[38]), "=f"(d[39]), "=f"(d[40]), "=f"(d[41]), "=f"(d[42]), "=f"(d[43]), "=f"(d[44]), "=f"(d[45]), "=f"(d[46]), "=f"(d[47]), "=f"(d[48]), "=f"(d[49]), "=f"(d[50]), "=f"(d[51]), "=f"(d[52]), "=f"(d[53]), "=f"(d[54]), "=f"(d[55])
    : "l"(da), "l"(db), "n"(TA), "n"(TB));
}
template <int TA, int TB> DEVI void wg_ss64(float* d, uint64_t da, uint64_t db) {
  asm volatile("wgmma.mma_async.sync.aligned.m64n64k16.f32.bf16.bf16 {%0,%1,%2,%3,%4,%5,%6,%7,%8,%9,%10,%11,%12,%13,%14,%15,%16,%17,%18,%19,%20,%21,%22,%23,%24,%25,%26,%27,%28,%29,%30,%31}, %32, %33, 1, 1, 1, %34, %35;"
    : "+f"(d[0]), "+f"(d[1]), "+f"(d[2]), "+f"(d[3]), "+f"(d[4]), "+f"(d[5]), "+f"(d[6]), "+f"(d[7]), "+f"(d[8]), "+f"(d[9]), "+f"(d[10]), "+f"(d[11]), "+f"(d[12]), "+f"(d[13]), "+f"(d[14]), "+f"(d[15]), "+f"(d[16]), "+f"(d[17]), "+f"(d[18]), "+f"(d[19]), "+f"(d[20]), "+f"(d[21]), "+f"(d[22]), "+f"(d[23]), "+f"(d[24]), "+f"(d[25]), "+f"(d[26]), "+f"(d[27]), "+f"(d[28]), "+f"(d[29]), "+f"(d[30]), "+f"(d[31])
    : "l"(da), "l"(db), "n"(TA), "n"(TB));
}
template <int TA, int TB> DEVI void wg_ss64z(float* d, uint64_t da, uint64_t db) {
  asm volatile("wgmma.mma_async.sync.aligned.m64n64k16.f32.bf16.bf16 {%0,%1,%2,%3,%4,%5,%6,%7,%8,%9,%10,%11,%12,%13,%14,%15,%16,%17,%18,%19,%20,%21,%22,%23,%24,%25,%26,%27,%28,%29,%30,%31}, %32, %33, 0, 1, 1, %34, %35;"
    : "=f"(d[0]), "=f"(d[1]), "=f"(d[2]), "=f"(d[3]), "=f"(d[4]), "=f"(d[5]), "=f"(d[6]), "=f"(d[7]), "=f"(d[8]), "=f"(d[9]), "=f"(d[10]), "=f"(d[11]), "=f"(d[12]), "=f"(d[13]), "=f"(d[14]), "=f"(d[15]), "=f"(d[16]), "=f"(d[17]), "=f"(d[18]), "=f"(d[19]), "=f"(d[20]), "=f"(d[21]), "=f"(d[22]), "=f"(d[23]), "=f"(d[24]), "=f"(d[25]), "=f"(d[26]), "=f"(d[27]), "=f"(d[28]), "=f"(d[29]), "=f"(d[30]), "=f"(d[31])
    : "l"(da), "l"(db), "n"(TA), "n"(TB));
}
template <int TB> DEVI void wg_rs168(float* d, const uint32_t* a, uint64_t db) {
  asm volatile("wgmma.mma_async.sync.aligned.m64n168k16.f32.bf16.bf16 {%0,%1,%2,%3,%4,%5,%6,%7,%8,%9,%10,%11,%12,%13,%14,%15,%16,%17,%18,%19,%20,%21,%22,%23,%24,%25,%26,%27,%28,%29,%30,%31,%32,%33,%34,%35,%36,%37,%38,%39,%40,%41,%42,%43,%44,%45,%46,%47,%48,%49,%50,%51,%52,%53,%54,%55,%56,%57,%58,%59,%60,%61,%62,%63,%64,%65,%66,%67,%68,%69,%70,%71,%72,%73,%74,%75,%76,%77,%78,%79,%80,%81,%82,%83}, {%84,%85,%86,%87}, %88, 1, 1, 1, %89;"
    : "+f"(d[0]), "+f"(d[1]), "+f"(d[2]), "+f"(d[3]), "+f"(d[4]), "+f"(d[5]), "+f"(d[6]), "+f"(d[7]), "+f"(d[8]), "+f"(d[9]), "+f"(d[10]), "+f"(d[11]), "+f"(d[12]), "+f"(d[13]), "+f"(d[14]), "+f"(d[15]), "+f"(d[16]), "+f"(d[17]), "+f"(d[18]), "+f"(d[19]), "+f"(d[20]), "+f"(d[21]), "+f"(d[22]), "+f"(d[23]), "+f"(d[24]), "+f"(d[25]), "+f"(d[26]), "+f"(d[27]), "+f"(d[28]), "+f"(d[29]), "+f"(d[30]), "+f"(d[31]), "+f"(d[32]), "+f"(d[33]), "+f"(d[34]), "+f"(d[35]), "+f"(d[36]), "+f"(d[37]), "+f"(d[38]), "+f"(d[39]), "+f"(d[40]), "+f"(d[41]), "+f"(d[42]), "+f"(d[43]), "+f"(d[44]), "+f"(d[45]), "+f"(d[46]), "+f"(d[47]), "+f"(d[48]), "+f"(d[49]), "+f"(d[50]), "+f"(d[51]), "+f"(d[52]), "+f"(d[53]), "+f"(d[54]), "+f"(d[55]), "+f"(d[56]), "+f"(d[57]), "+f"(d[58]), "+f"(d[59]), "+f"(d[60]), "+f"(d[61]), "+f"(d[62]), "+f"(d[63]), "+f"(d[64]), "+f"(d[65]), "+f"(d[66]), "+f"(d[67]), "+f"(d[68]), "+f"(d[69]), "+f"(d[70]), "+f"(d[71]), "+f"(d[72]), "+f"(d[73]), "+f"(d[74]), "+f"(d[75]), "+f"(d[76]), "+f"(d[77]), "+f"(d[78]), "+f"(d[79]), "+f"(d[80]), "+f"(d[81]), "+f"(d[82]), "+f"(d[83])
    : "r"(a[0]), "r"(a[1]), "r"(a[2]), "r"(a[3]), "l"(db), "n"(TB));
}
template <int TB> DEVI void wg_rs168z(float* d, const uint32_t* a, uint64_t db) {
  asm volatile("wgmma.mma_async.sync.aligned.m64n168k16.f32.bf16.bf16 {%0,%1,%2,%3,%4,%5,%6,%7,%8,%9,%10,%11,%12,%13,%14,%15,%16,%17,%18,%19,%20,%21,%22,%23,%24,%25,%26,%27,%28,%29,%30,%31,%32,%33,%34,%35,%36,%37,%38,%39,%40,%41,%42,%43,%44,%45,%46,%47,%48,%49,%50,%51,%52,%53,%54,%55,%56,%57,%58,%59,%60,%61,%62,%63,%64,%65,%66,%67,%68,%69,%70,%71,%72,%73,%74,%75,%76,%77,%78,%79,%80,%81,%82,%83}, {%84,%85,%86,%87}, %88, 0, 1, 1, %89;"
    : "=f"(d[0]), "=f"(d[1]), "=f"(d[2]), "=f"(d[3]), "=f"(d[4]), "=f"(d[5]), "=f"(d[6]), "=f"(d[7]), "=f"(d[8]), "=f"(d[9]), "=f"(d[10]), "=f"(d[11]), "=f"(d[12]), "=f"(d[13]), "=f"(d[14]), "=f"(d[15]), "=f"(d[16]), "=f"(d[17]), "=f"(d[18]), "=f"(d[19]), "=f"(d[20]), "=f"(d[21]), "=f"(d[22]), "=f"(d[23]), "=f"(d[24]), "=f"(d[25]), "=f"(d[26]), "=f"(d[27]), "=f"(d[28]), "=f"(d[29]), "=f"(d[30]), "=f"(d[31]), "=f"(d[32]), "=f"(d[33]), "=f"(d[34]), "=f"(d[35]), "=f"(d[36]), "=f"(d[37]), "=f"(d[38]), "=f"(d[39]), "=f"(d[40]), "=f"(d[41]), "=f"(d[42]), "=f"(d[43]), "=f"(d[44]), "=f"(d[45]), "=f"(d[46]), "=f"(d[47]), "=f"(d[48]), "=f"(d[49]), "=f"(d[50]), "=f"(d[51]), "=f"(d[52]), "=f"(d[53]), "=f"(d[54]), "=f"(d[55]), "=f"(d[56]), "=f"(d[57]), "=f"(d[58]), "=f"(d[59]), "=f"(d[60]), "=f"(d[61]), "=f"(d[62]), "=f"(d[63]), "=f"(d[64]), "=f"(d[65]), "=f"(d[66]), "=f"(d[67]), "=f"(d[68]), "=f"(d[69]), "=f"(d[70]), "=f"(d[71]), "=f"(d[72]), "=f"(d[73]), "=f"(d[74]), "=f"(d[75]), "=f"(d[76]), "=f"(d[77]), "=f"(d[78]), "=f"(d[79]), "=f"(d[80]), "=f"(d[81]), "=f"(d[82]), "=f"(d[83])
    : "r"(a[0]), "r"(a[1]), "r"(a[2]), "r"(a[3]), "l"(db), "n"(TB));
}
template <int TB> DEVI void wg_rs112(float* d, const uint32_t* a, uint64_t db) {
  asm volatile("wgmma.mma_async.sync.aligned.m64n112k16.f32.bf16.bf16 {%0,%1,%2,%3,%4,%5,%6,%7,%8,%9,%10,%11,%12,%13,%14,%15,%16,%17,%18,%19,%20,%21,%22,%23,%24,%25,%26,%27,%28,%29,%30,%31,%32,%33,%34,%35,%36,%37,%38,%39,%40,%41,%42,%43,%44,%45,%46,%47,%48,%49,%50,%51,%52,%53,%54,%55}, {%56,%57,%58,%59}, %60, 1, 1, 1, %61;"
    : "+f"(d[0]), "+f"(d[1]), "+f"(d[2]), "+f"(d[3]), "+f"(d[4]), "+f"(d[5]), "+f"(d[6]), "+f"(d[7]), "+f"(d[8]), "+f"(d[9]), "+f"(d[10]), "+f"(d[11]), "+f"(d[12]), "+f"(d[13]), "+f"(d[14]), "+f"(d[15]), "+f"(d[16]), "+f"(d[17]), "+f"(d[18]), "+f"(d[19]), "+f"(d[20]), "+f"(d[21]), "+f"(d[22]), "+f"(d[23]), "+f"(d[24]), "+f"(d[25]), "+f"(d[26]), "+f"(d[27]), "+f"(d[28]), "+f"(d[29]), "+f"(d[30]), "+f"(d[31]), "+f"(d[32]), "+f"(d[33]), "+f"(d[34]), "+f"(d[35]), "+f"(d[36]), "+f"(d[37]), "+f"(d[38]), "+f"(d[39]), "+f"(d[40]), "+f"(d[41]), "+f"(d[42]), "+f"(d[43]), "+f"(d[44]), "+f"(d[45]), "+f"(d[46]), "+f"(d[47]), "+f"(d[48]), "+f"(d[49]), "+f"(d[50]), "+f"(d[51]), "+f"(d[52]), "+f"(d[53]), "+f"(d[54]), "+f"(d[55])
    : "r"(a[0]), "r"(a[1]), "r"(a[2]), "r"(a[3]), "l"(db), "n"(TB));
}
template <int TB> DEVI void wg_rs112z(float* d, const uint32_t* a, uint64_t db) {
  asm volatile("wgmma.mma_async.sync.aligned.m64n112k16.f32.bf16.bf16 {%0,%1,%2,%3,%4,%5,%6,%7,%8,%9,%10,%11,%12,%13,%14,%15,%16,%17,%18,%19,%20,%21,%22,%23,%24,%25,%26,%27,%28,%29,%30,%31,%32,%33,%34,%35,%36,%37,%38,%39,%40,%41,%42,%43,%44,%45,%46,%47,%48,%49,%50,%51,%52,%53,%54,%55}, {%56,%57,%58,%59}, %60, 0, 1, 1, %61;"
    : "=f"(d[0]), "=f"(d[1]), "=f"(d[2]), "=f"(d[3]), "=f"(d[4]), "=f"(d[5]), "=f"(d[6]), "=f"(d[7]), "=f"(d[8]), "=f"(d[9]), "=f"(d[10]), "=f"(d[11]), "=f"(d[12]), "=f"(d[13]), "=f"(d[14]), "=f"(d[15]), "=f"(d[16]), "=f"(d[17]), "=f"(d[18]), "=f"(d[19]), "=f"(d[20]), "=f"(d[21]), "=f"(d[22]), "=f"(d[23]), "=f"(d[24]), "=f"(d[25]), "=f"(d[26]), "=f"(d[27]), "=f"(d[28]), "=f"(d[29]), "=f"(d[30]), "=f"(d[31]), "=f"(d[32]), "=f"(d[33]), "=f"(d[34]), "=f"(d[35]), "=f"(d[36]), "=f"(d[37]), "=f"(d[38]), "=f"(d[39]), "=f"(d[40]), "=f"(d[41]), "=f"(d[42]), "=f"(d[43]), "=f"(d[44]), "=f"(d[45]), "=f"(d[46]), "=f"(d[47]), "=f"(d[48]), "=f"(d[49]), "=f"(d[50]), "=f"(d[51]), "=f"(d[52]), "=f"(d[53]), "=f"(d[54]), "=f"(d[55])
    : "r"(a[0]), "r"(a[1]), "r"(a[2]), "r"(a[3]), "l"(db), "n"(TB));
}
#define PD2 1500
#define RPD 6000
#define HOLDN 1
#define NPROBE 3
constexpr int PREP_SMEM = 57344 + 5 * 32768 + 128 + 1024;
__global__ void __launch_bounds__(384, 1) prep_kernel(const __grid_constant__ CUtensorMap mq, const __grid_constant__ CUtensorMap mk,
                                                      const __grid_constant__ CUtensorMap mv, const __grid_constant__ CUtensorMap mo,
                                                      const uint4* __restrict__ wqkv, const uint4* __restrict__ wo, const uint32_t* __restrict__ mem0) {
  extern __shared__ __align__(1024) char smem_raw[];
  const uint32_t sb = (smem_u32(smem_raw) + 1023) & ~1023u;
  const int warp = __shfl_sync(0xffffffffu, threadIdx.x >> 5, 0), lane = threadIdx.x & 31;
  const int type = blockIdx.x >> 6, h = (blockIdx.x >> 2) & 15, nq = blockIdx.x & 3, wg = warp >> 2;
  const uint32_t bars = sb + 57344 + 5 * 32768, abuf = sb + 57344;
  GT(blockIdx.x == 0 && threadIdx.x == 0, 1);
  if (threadIdx.x == 0) { for (int i = 0; i < 8; i++) mbar_init(bars + i * 8, 1); asm volatile("fence.mbarrier_init.release.cluster;" ::: "memory"); }
  if (warp >= 10) {
    const int it = blockIdx.x * 2 + warp - 10;
    if (it < 224) {
      delay_until(clk32() + RPD);
      const int c = (it >> 2) * 4 + (lane >> 3), kk = (it & 3) * 8 + (lane & 7), rs = c < 168 ? 168 : 56, ds = c < 168 ? 672 : 448;
      const uint4* src = (c < 168 ? wqkv + c : wo + c - 168) + kk * rs;
      uint4* dst = (c < 168 ? g_aw + ((c % 56) / 7 * 294 + c / 56 * 7 + c % 7) * 32 : g_aw + D * 168 + ((c - 168) / 14 * 196 + (c - 168) % 14) * 32) + kk;
      uint4 v[14];
      #pragma unroll
      for (int i = 0; i < 14; i++) v[i] = __ldg(src + i * 32 * rs);
      #pragma unroll
      for (int i = 0; i < 14; i++) dst[i * ds] = v[i];
    }
    return;
  }
  if (warp >= 8) {
    uint32_t smid; asm volatile("mov.u32 %0, %%smid;" : "=r"(smid));
    unsigned* pa = (unsigned*)(acc_base() + 196608 + (warp - 8) * 4096 + (smid & 127) * 32);
    if (lane < 8) pa[lane] = 0;
    unsigned best = 0xffffffffu;
    unsigned v = 0;
    #pragma unroll 1
    for (int i = 0; i < NPROBE; i++) {
      unsigned t0 = 0, t1 = 0;
      if (lane == 0) { t0 = clk32(); v = atomicExch(pa + v, 0); }
      if (i == HOLDN) { __syncwarp(); bar_arrive<4, 320>(); }
      asm volatile("{.reg .pred p; setp.eq.u32 p, %1, 0; @p mov.u32 %0, %%clock;}" : "+r"(t1) : "r"(v) : "memory");
      best = min(best, t1 - t0);
    }
    if (warp == 9 && lane == 0) sts32(bars + 64, best);
    __syncwarp();
    if (HOLDN >= NPROBE) bar_arrive<4, 320>();
    bar_sync<3, 64>();
    if (warp == 8 && lane == 0) {
      if (smid < 156) g_side[smid] = min(max((int)(best - lds32(bars + 64)), -250), 250);
      if (blockIdx.x == 0) g_side[156] = g_side[157] = 0;
      __threadfence();
      asm volatile("griddepcontrol.launch_dependents;" ::: "memory");
    }
    return;
  }
  if (threadIdx.x < 2) asm volatile("prefetch.tensormap [%0];" :: "l"(type == 0 ? (threadIdx.x ? &mq : &mk) : (threadIdx.x ? &mo : &mv)) : "memory");
  bar_sync<4, 320>();
  if (blockIdx.x >= 128) return;
  auto load_a = [&](int mt, int slot) {
    const int row = mt * 64;
    e_expect(bars + 8 + mt * 8, 32768);
    if (type == 0) e_tma3d(abuf + slot * 32768, &mq, 0, row, h * 4, bars + 8 + mt * 8);
    else e_tma2d(abuf + slot * 32768, &mo, row, h * 256, bars + 8 + mt * 8);
  };
  if (warp == 0) {
    e_expect(bars, 57344);
    e_tma3d(sb, type == 0 ? &mk : &mv, 0, nq * SL, h * 4, bars);
    for (int i = 0; i < 5; i++) { if (i == 2 && PD2) delay_until(clk32() + PD2); load_a(i, i); }
  }
  {
    const int gt = blockIdx.x * 256 + threadIdx.x;
    uint4 v = make_uint4(0, 0, 0, 0);
    if (gt < 2048 && !(gt & 8)) {
      const int q = gt >> 9, p = (gt >> 6) & 3, l = ((gt >> 4) & 3) * 8 + (gt & 7);
      const uint32_t* m = mem0 + (l >> 2) * 224 + q * 56 + (l & 3);
      v = make_uint4(m[8 * p], m[8 * p + 4], m[32 + 4 * p], ((m[48 + 4 * (p >> 1)] >> ((p & 1) * 16)) & 0xffffu) | CNT);
    }
    if (gt < 10240) ((uint4*)acc_base())[gt] = v;
  }
  const float sc = type == 0 ? 0.0625f * 1.4426950408889634f : 1.0f;
  mbar_wait(bars, 0);
  const uint64_t db = mkdesc(sb, 16, 1024, 1);
  for (int mt = wg; mt < 7; mt += 2) {
    const int slot = mt < 5 ? mt : 6 - mt;
    float d[56];
    mbar_wait(bars + 8 + mt * 8, 0);
    if (mt >= 1) bar_sync_id(5 + wg, 256);
    const uint64_t da = mkdesc(abuf + slot * 32768, 16, 1024, 1);
    wg_fence();
    if (type == 0) {
      #pragma unroll
      for (int k = 0; k < 16; k++) {
        if (k == 0) wg_ss112z<0, 0>(d, da, db); else wg_ss112<0, 0>(d, da + (k >> 2) * 512 + (k & 3) * 2, db + (k >> 2) * 896 + (k & 3) * 2);
      }
    } else {
      #pragma unroll
      for (int k = 0; k < 16; k++) {
        if (k == 0) wg_ss112z<1, 0>(d, da, db); else wg_ss112<1, 0>(d, da + k * 128, db + (k >> 2) * 896 + (k & 3) * 2);
      }
    }
    wg_commit();
    if (mt < 6) bar_arrive_id(6 - wg, 256);
    wg_wait<0>();
    acc_fence<56>(d);
    if (mt < 2) { bar_sync_id(1 + wg, 128); if ((warp & 3) == 0) load_a(6 - mt, mt); }
    uint4* dst = g_frag[type] + ((size_t)(h * 28 + mt * 4 + (warp & 3)) * 28 + 7 * nq) * 32 + lane;
    #pragma unroll
    for (int k = 0; k < 7; k++)
      dst[k * 32] = make_uint4(pack_bf(d[8 * k] * sc, d[8 * k + 1] * sc), pack_bf(d[8 * k + 2] * sc, d[8 * k + 3] * sc),
                               pack_bf(d[8 * k + 4] * sc, d[8 * k + 5] * sc), pack_bf(d[8 * k + 6] * sc, d[8 * k + 7] * sc));
  }
}
#define NOVA 3
#define NOVB 1
#define RDELAY 295
#define FDEP 1
#define WANC 3
#define VDEP 0
#define RPL 1
#define SXL 2
#define PVA 3
#define LASTX 1
#define PVB 2
#define SPEC 0
#define QPIN 4
#define C2P 46
#define C2Q 8
constexpr int XS_SZ = 28672;
constexpr int XA_OFF = 0;
constexpr int YS_OFF = 3 * 8192, YS_SZ = 14336;
constexpr int YT_OFF = YS_OFF + 3 * YS_SZ, YT_SZ = 7168;
constexpr int ZT_OFF = YT_OFF + 3 * YT_SZ;
constexpr int WT_OFF = ZT_OFF + 3 * YT_SZ;
constexpr int WP_OFF = WT_OFF + 8 * 2048;
constexpr int BOV_OFF = WP_OFF + 4 * 1792 + 256;
constexpr int ONES_OFF = BOV_OFF + 4 * NOVB * 512;
constexpr int MEM_OFF = ONES_OFF + 128, MEM_P = 912;
constexpr int AOV_OFF = MEM_OFF + 8 * MEM_P;
constexpr int ZER_OFF = AOV_OFF + 4 * NOVA * 512;
constexpr int DUMP_OFF = ZER_OFF + 128;
constexpr int RXX_OFF = DUMP_OFF + 256;
constexpr int LOC_OFF = RXX_OFF + 1024;
constexpr int RX2_OFF = LOC_OFF + 2048;
constexpr int PS_OFF = RX2_OFF + 5120;
constexpr int R_END = PS_OFF + 5120;
constexpr int BAR_OFF = 204800;
constexpr int TIM_OFF = BAR_OFF + 256;
constexpr int MAIN_SMEM = TIM_OFF + 16384 + 1024;
static_assert(R_END <= BAR_OFF, "smem");
enum { B_MEM = 2, B_RP, B_W, B_RED, B_LOC, B_END, B_PAIR };
#define TIM(i)

DEVI float quad_max(float s0, float s1, uint32_t x0, uint32_t x1, uint32_t x2, uint32_t x3) {
  uint32_t xm; asm("{.reg .b32 a, b; max.bf16x2 a, %1, %2; max.bf16x2 b, %3, %4; max.bf16x2 %0, a, b;}" : "=r"(xm) : "r"(x0), "r"(x1), "r"(x2), "r"(x3));
  const float mx = fmaxf(fmaxf(bf_lo(xm), bf_hi(xm)), fmaxf(s0, s1));
  const float m1 = __shfl_xor_sync(0xffffffffu, mx, 1), m2 = __shfl_xor_sync(0xffffffffu, mx, 2), m3 = __shfl_xor_sync(0xffffffffu, mx, 3);
  return fmaxf(fmaxf(mx, m1), fmaxf(m2, m3));
}
DEVI void probs_sum(uint32_t sb, int s, int lane, float (&e)[5][4]) {
  mbar_wait(sb + BAR_OFF + 96 + (s & 1) * 8, ((s + 1) >> 1) & 1);
  const int dg = (lane >> 2) - 2 * (lane & 3);
  const uint32_t id = dg == 0 ? 0x3f80u : dg == 1 ? 0x3f800000u : 0u;
  #pragma unroll
  for (int i = 0; i < 5; i++) {
    uint32_t b0, b1, b2, b3;
    ldsm4t(sb + RX2_OFF + (s & 1) * 2560 + i * 512 + lane * 16, b0, b1, b2, b3);
    mma16816z(e[i], id, id, id, id, b0, b1); mma16816(e[i], id, id, id, id, b2, b3);
  }
}
DEVI void probs_fin(uint32_t sb, int s, int j, int lane, float (&e)[5][4]) {
  const int lim = 8 * j + (lane >> 2) - 2 * (lane & 3);
  float mx = fmaxf(e[0][0], e[0][1]);
  #pragma unroll
  for (int i = 1; i < 5; i++) {
    if (8 * i - 8 > lim) e[i][0] = -INFINITY;
    if (8 * i - 7 > lim) e[i][1] = -INFINITY;
    mx = fmaxf(mx, fmaxf(e[i][0], e[i][1]));
  }
  { const float m1 = __shfl_xor_sync(0xffffffffu, mx, 1), m2 = __shfl_xor_sync(0xffffffffu, mx, 2), m3 = __shfl_xor_sync(0xffffffffu, mx, 3);
    mx = fmaxf(fmaxf(mx, m1), fmaxf(m2, m3)); }
  #pragma unroll
  for (int i = 0; i < 5; i++) { e[i][0] = ex2(e[i][0] - mx); e[i][1] = ex2(e[i][1] - mx); }
  float sum = (((e[0][0] + e[0][1]) + (e[1][0] + e[1][1])) + ((e[2][0] + e[2][1]) + (e[3][0] + e[3][1]))) + (e[4][0] + e[4][1]);
  { const float s1 = __shfl_xor_sync(0xffffffffu, sum, 1), s2 = __shfl_xor_sync(0xffffffffu, sum, 2), s3 = __shfl_xor_sync(0xffffffffu, sum, 3);
    sum = (sum + s1) + (s2 + s3); }
  const float inv = rcpf(sum);
  #pragma unroll
  for (int i = 0; i < 5; i++) sts32(sb + PS_OFF + (s & 7) * 640 + i * 128 + lane * 4, pack_bf(e[i][0] * inv, e[i][1] * inv));
}

DEVI void sum4(uint32_t src, uint32_t dst, int lane) {
    const uint32_t a = src + lane * 16;
    const uint4 u0 = lds128(a), u1 = lds128(a + 1792), u2 = lds128(a + 3584), u3 = lds128(a + 5376);
#define RSUM(c) pack_bf((bf_lo(u0.c) + bf_lo(u1.c)) + (bf_lo(u2.c) + bf_lo(u3.c)), (bf_hi(u0.c) + bf_hi(u1.c)) + (bf_hi(u2.c) + bf_hi(u3.c)))
    sts128(dst + lane * 16, make_uint4(RSUM(x), RSUM(y), RSUM(z), RSUM(w)));
}

DEVI void r_score(uint32_t sb, int h, int j, int side, int warp, int lane) {
  const int q = warp;
  uint32_t aw[49 - NOVA][4];
  #pragma unroll
  for (int i = 0; i < 49; i++) {
    const uint4 x = g_frag[0][((size_t)(h * 28 + 7 * j + i % 7) * 28 + 7 * q + i / 7) * 32 + lane];
    if (i >= NOVA) { aw[i >= NOVA ? i - NOVA : 0][0] = x.x; aw[i >= NOVA ? i - NOVA : 0][1] = x.y; aw[i >= NOVA ? i - NOVA : 0][2] = x.z; aw[i >= NOVA ? i - NOVA : 0][3] = x.w; }
    else sts128(sb + AOV_OFF + (q * NOVA + i) * 512 + lane * 16, x);
  }
  uint4 w[4];
  #pragma unroll
  for (int i = 0; i < 4; i++) w[i] = make_uint4(0, 0, 0, CNT);
  const uint32_t d2m = sb + BAR_OFF + 88;
  const uint32_t a_m = sb + MEM_OFF + (lane & 7) * MEM_P + (lane >> 3) * 16;
  const char* rp = acc_base();
  int sl = 2;
  const uint32_t a_s0 = a_m + 224 * q;
  uint4 ov[NOVA];
  auto load_ov = [&]() {
    #pragma unroll
    for (int i = 0; i < NOVA; i++) ov[i] = lds128(sb + AOV_OFF + (q * NOVA + i) * 512 + lane * 16);
  };
  load_ov();
  GTL(h == 1 && j == 1 && q == 0 && lane == 0, 6);
  for (int s = -1; s < NSEG; s++) {
    float acc[7][4];
    auto head = [&]() {
      #pragma unroll
      for (int i = 0; i < SPEC; i++) {
        const int m = i % 7, f = i >= NOVA ? i - NOVA : 0;
        if (i < NOVA) mma16816z(acc[m], ov[i < NOVA ? i : 0].x, ov[i < NOVA ? i : 0].y, ov[i < NOVA ? i : 0].z, ov[i < NOVA ? i : 0].w, w[0].x, w[0].y);
        else if (i < 7) mma16816z(acc[m], aw[f][0], aw[f][1], aw[f][2], aw[f][3], w[0].x, w[0].y);
        else mma16816(acc[m], aw[f][0], aw[f][1], aw[f][2], aw[f][3], w[i / 7].x, w[i / 7].y);
      }
    };
    head();
    if (__builtin_expect(__any_sync(0xffffffffu, (w[0].w & w[1].w & w[2].w & w[3].w & CNT) != CNT), 0)) {
      if (SPEC) load_ov();
      int spin = 0;
      do {
        #pragma unroll
        for (int i = 0; i < 4; i++) w[i] = ldg128_relaxed(rp + i * 1024);
        if (++spin > SPIN_LIMIT) __trap();
      } while (__any_sync(0xffffffffu, (w[0].w & w[1].w & w[2].w & w[3].w & CNT) != CNT));
      head();
    }
    TIM(0);
    uint32_t mb[14];
    mb[0] = w[0].x; mb[1] = w[0].y; mb[2] = w[1].x; mb[3] = w[1].y; mb[4] = w[2].x; mb[5] = w[2].y; mb[6] = w[3].x; mb[7] = w[3].y;
    mb[8] = w[0].z; mb[9] = w[1].z; mb[10] = w[2].z; mb[11] = w[3].z; mb[12] = __byte_perm(w[0].w, w[1].w, 0x5410); mb[13] = __byte_perm(w[2].w, w[3].w, 0x5410);
    #pragma unroll
    for (int i = 0; i < 4; i++) stsm2(a_s0 + 32 * i, mb[2 * i], mb[2 * i + 1]);
    stsm4(a_s0 + 128, mb[8], mb[9], mb[10], mb[11]); stsm2(a_s0 + 192, mb[12], mb[13]);
    bar_arrive_id(B_PAIR + q, 64);
    const uint32_t zr = lds32(sb + ZER_OFF);
    OPAQUE(lane);
    uint32_t qa[14];
    #pragma unroll
    for (int i = SPEC; i < 49; i++) {
      const int m = i % 7, ks = i / 7, f = i >= NOVA ? i - NOVA : 0;
      if (i == (SPEC > 7 ? SPEC : 7)) {
        bar_sync<B_MEM, 128>();
        const uint32_t a = a_m + 224 * j;
        ldsm4(a, qa[0], qa[1], qa[2], qa[3]); ldsm4(a + 64, qa[4], qa[5], qa[6], qa[7]); ldsm4(a + 128, qa[8], qa[9], qa[10], qa[11]);
        mb[2 * QPIN] |= (qa[0] | qa[4] | qa[8]) & zr;
      }
      if (i == C2P) {
        sts32(sb + DUMP_OFF, __float_as_uint(acc[m][0]));
        bar_arrive_id(B_PAIR + 4 + q, 64);
        ldsm2(a_m + 224 * j + 192, qa[12], qa[13]);
        qa[C2Q] |= qa[12] & zr;
      }
      if (FDEP && i == 7 * FDEP) {
        uint32_t t = 0;
        #pragma unroll
        for (int e = 0; e < 7; e++) t |= __float_as_uint(acc[e][0]);
        mb[2 * (ks + 1)] |= t & zr;
      }
      if (i < NOVA) mma16816z(acc[m], ov[i < NOVA ? i : 0].x, ov[i < NOVA ? i : 0].y, ov[i < NOVA ? i : 0].z, ov[i < NOVA ? i : 0].w, mb[0], mb[1]);
      else if (ks == 0) mma16816z(acc[m], aw[f][0], aw[f][1], aw[f][2], aw[f][3], mb[0], mb[1]);
      else mma16816(acc[m], aw[f][0], aw[f][1], aw[f][2], aw[f][3], mb[2 * ks], mb[2 * ks + 1]);
    }
    uint32_t pk[14];
    {
      float se[4], so[4], te[4], to[4];
      #pragma unroll
      for (int i = 0; i < 14; i++) pk[i] = pack_bf(acc[i >> 1][2 * (i & 1)], acc[i >> 1][2 * (i & 1) + 1]);
      mma16816z(se, qa[0], qa[1], qa[2], qa[3], movm(pk[0]), movm(pk[2])); mma16816z(so, qa[0], qa[1], qa[2], qa[3], movm(pk[1]), movm(pk[3]));
      mma16816z(te, qa[4], qa[5], qa[6], qa[7], movm(pk[4]), movm(pk[6])); mma16816z(to, qa[4], qa[5], qa[6], qa[7], movm(pk[5]), movm(pk[7]));
      mma16816(se, qa[8], qa[9], qa[10], qa[11], movm(pk[8]), movm(pk[10])); mma16816(so, qa[8], qa[9], qa[10], qa[11], movm(pk[9]), movm(pk[11]));
      mma1688(te, qa[12], qa[13], movm(pk[12])); mma1688(to, qa[12], qa[13], movm(pk[13]));
      sts64f(sb + LOC_OFF + 1024 + q * 256 + lane * 8, (se[0] + so[2]) + (te[0] + to[2]), (se[1] + so[3]) + (te[1] + to[3]));
    }
    TIM(1);
    GTL(h == 1 && j == 1 && q == 0 && s == 0 && lane == 0, 16);
    const uint32_t r0 = (j + 1 + (q & 1)) & 3, r1 = (j + 3 + (q & 1)) & 3, l_addr = sb + RXX_OFF + (q >> 1) * 512 + j * 128 + lane * 4;
    uint32_t ra0 = mapa(l_addr, r0), rb0 = mapa(d2m, r0), ra1 = mapa(l_addr, r1), rb1 = mapa(d2m, r1), a_loc = sb + LOC_OFF + (q >> 1) * 1024 + lane * 8;
    asm volatile("" : "+r"(ra0), "+r"(rb0), "+r"(ra1), "+r"(rb1), "+r"(a_loc));
    bar_sync<B_LOC, 256>();
    {
      const uint2 p0 = lds64(a_loc), p1 = lds64(a_loc + 256), p2 = lds64(a_loc + 512), p3 = lds64(a_loc + 768);
#define SUM4(c) ((__uint_as_float(p0.c) + __uint_as_float(p1.c)) + (__uint_as_float(p2.c) + __uint_as_float(p3.c)))
      const uint32_t sv = pack_bf(SUM4(x), SUM4(y));
      st_async32(ra0, sv, rb0); st_async32(ra1, sv, rb1);
      asm volatile("{.reg .pred p; setp.eq.s32 p, %1, 0; @p mbarrier.arrive.expect_tx.shared::cta.b64 _, [%0], 1024;}" :: "r"(d2m), "r"(q | lane) : "memory");
    }
    auto put_rp = [&]() {
      const uint32_t a_rp = sb + YS_OFF + sl * YS_SZ + (4 + q) * 1792 + lane * 16;
      stsm4(a_rp, pk[0], pk[1], pk[2], pk[3]); stsm4(a_rp + 512, pk[4], pk[5], pk[6], pk[7]); stsm4(a_rp + 1024, pk[8], pk[9], pk[10], pk[11]); stsm2(a_rp + 1536, pk[12], pk[13]);
      bar_arrive<B_RP, 256>();
    };
    if (RPL == 0) put_rp();
    TIM(2);
    const uint32_t zb = sb + ZT_OFF + sl * YT_SZ;
    const int r8 = lane & 7, i4 = lane >> 3;
    const uint32_t c3 = 8 * (12 + (q >> 1)) + r8 + (q & 1);
    const uint32_t ones = sb + ONES_OFF + ((q & 1) ? 0 : 16);
    uint32_t zf[4][4];
    #pragma unroll
    for (int i = 0; i < 3; i++) ldsm4(zb + i4 * 1792 + (8 * (i < 2 ? 2 * q + i : 8 + q) + r8) * 16, zf[i][0], zf[i][1], zf[i][2], zf[i][3]);
    ldsm4((r8 & 1) ? ones : zb + i4 * 1792 + c3 * 16, zf[3][0], zf[3][1], zf[3][2], zf[3][3]);
    if (RPL == 1) put_rp();
    const uint32_t goff = i4 * 256 + r8 * 16;
    const char* accw = acc_base() + (acc_off(s < 0 ? 7 : s + 1, j, side) + q * 1024) + goff;
    uint32_t a_w = sb + WP_OFF + i4 * 1792 + r8 * 16;
    uint32_t a_w3 = (r8 & 1) ? (i4 == 0 ? ones : sb + ZER_OFF + ((q & 1) ? 0 : 16)) : sb + WP_OFF + i4 * 1792 + c3 * 16;
    uint32_t a_rx = sb + RXX_OFF + lane * 16;
    asm volatile("" : "+r"(a_w), "+r"(a_w3), "+r"(a_rx), "+l"(accw));
    if (LASTX && s == NSEG - 1) { bar_sync<B_W, 256>(); bar_arrive<B_RED, 256>(); mbar_wait(d2m, 0); break; }
    TIM(3);
    mbar_wait(d2m, (s + 1) & 1);
    TIM(4);
    GTL(h == 1 && j == 1 && q == 0 && s == 0 && lane == 0, 18);
    uint32_t x0, x1, x2, x3, v0, v1, v2, v3;
    ldsm4(a_rx + 512, v0, v1, v2, v3);
    ldsm4(a_rx, x0, x1, x2, x3);
    const float s0 = (bf_lo(v0) + bf_lo(v1)) + (bf_lo(v2) + bf_lo(v3)), s1 = (bf_hi(v0) + bf_hi(v1)) + (bf_hi(v2) + bf_hi(v3));
    const float mx = quad_max(s0, s1, x0, x1, x2, x3);
    sts32(sb + DUMP_OFF, WANC == 0 ? __float_as_uint(s0) : WANC == 1 ? __float_as_uint(mx) : WANC == 2 ? x0 : __float_as_uint(fmaxf(s0, s1)));
    bar_sync<B_W, 256>();
    uint32_t wf[4][4];
    ldsm4(a_w3, wf[3][0], wf[3][1], wf[3][2], wf[3][3]);
    #pragma unroll
    for (int i = 2; i >= 0; i--) ldsm4(a_w + (i < 2 ? 2 * q + i : 8 + q) * 128, wf[i][0], wf[i][1], wf[i][2], wf[i][3]);
    const uint32_t p1 = pack_bf(ex2(bf_lo(x0) - mx), ex2(bf_hi(x0) - mx)), p2 = pack_bf(ex2(bf_lo(x1) - mx), ex2(bf_hi(x1) - mx));
    const uint32_t p3 = pack_bf(ex2(bf_lo(x2) - mx), ex2(bf_hi(x2) - mx)), p4 = pack_bf(ex2(bf_lo(x3) - mx), ex2(bf_hi(x3) - mx));
    const uint32_t p0 = pack_bf(ex2(s0 - mx), ex2(s1 - mx));
    TIM(5);
    float o[4][4], u[4][4];
    #pragma unroll
    for (int i = 3; i >= 0; i--) { mma16816z(o[i], p0, p0, p0, p0, wf[i][0], wf[i][1]); mma16816z(u[i], p0, p0, p0, p0, wf[i][2], wf[i][3]); }
    #pragma unroll
    for (int i = 3; i >= 0; i--) {
      if (PVA && i == 2) zf[PVA - 1][PVB & 2] |= __float_as_uint((PVB & 1) ? o[3][0] : u[0][0]) & zr;
      mma16816(o[i], p1, p3, p2, p4, zf[i][0], zf[i][1]); mma16816(u[i], p1, p3, p2, p4, zf[i][2], zf[i][3]);
    }
    #pragma unroll
    for (int i = 3; i >= 0; i--) { o[i][0] += u[i][2]; o[i][1] += u[i][3]; }
    const float inv = rcpf(o[3][1]);
    const uint32_t w0 = pack_bf(o[0][0] * inv, o[0][1] * inv), w1 = pack_bf(o[1][0] * inv, o[1][1] * inv), w2 = pack_bf(o[2][0] * inv, o[2][1] * inv), w3 = pack_bf(o[3][0] * inv, 1.0f);
    asm volatile("red.relaxed.gpu.global.add.noftz.v4.bf16x2 [%0], {%1,%2,%3,%4};" :: "l"(accw), "r"(w0), "r"(w1), "r"(w2), "r"(w3) : "memory");
    const unsigned tp = clk32() + RDELAY;
    bar_arrive<B_RED, 256>();
    if (__builtin_expect((unsigned)s >= NSEG - 1, 0)) {
      if (s >= 0) break;
      cluster_sync_relaxed();
    }
    OPAQUE(lane);
    TIM(6);
    GTL(h == 1 && j == 1 && q == 0 && s >= 0 && ((s & 7) == 0 || s < 8), (s & 7) == 0 ? 8 + (s >> 3) : 24 + s);
    rp = acc_base() + acc_off(s + 1, q, side) + goff;
    if (++sl == 3) sl = 0;
    asm volatile("" : "+l"(rp));
    load_ov();
    delay_until(tp);
    TIM(7);
    #pragma unroll
    for (int i = 0; i < 4; i++) w[i] = ldg128_relaxed(rp + i * 1024);
    sum4(sb + WP_OFF + q * 512, sb + WT_OFF + (s & 7) * 2048 + q * 512, lane);
  }
  sum4(sb + WP_OFF + q * 512, sb + WT_OFF + 7 * 2048 + q * 512, lane);
  fence_async_smem();
  bar_arrive<B_END, 160>();
}

DEVI void r_value(const CUtensorMap* xmap, const CUtensorMap* ymap, const CUtensorMap* zmap, uint32_t sb, int h, int j, int side, int warp, int lane) {
  const int v = warp - 4;
  uint32_t bw[49 - NOVB][4];
  #pragma unroll
  for (int i = 0; i < 49; i++) {
    const uint4 x = g_frag[1][((size_t)(h * 28 + 7 * j + i % 7) * 28 + 7 * v + i / 7) * 32 + lane];
    if (i < 49 - NOVB) { bw[i < 49 - NOVB ? i : 0][0] = x.x; bw[i < 49 - NOVB ? i : 0][1] = x.y; bw[i < 49 - NOVB ? i : 0][2] = x.z; bw[i < 49 - NOVB ? i : 0][3] = x.w; }
    else sts128(sb + BOV_OFF + (v * NOVB + i - (49 - NOVB)) * 512 + lane * 16, x);
  }
  const uint32_t tfull = sb + BAR_OFF, d2t = sb + BAR_OFF + 96;
  unsigned* const vflag = vflag_ptr(side);
  const unsigned* const tflag = tflag_ptr(side) + h;
  auto load_kv = [&](int s, int sl, bool late) {
    if (__builtin_expect(late, 0)) { wait_flag<0>(tflag + s * NH, TFLAG_N); fence_async_global(); }
    e_g2s(sb + YT_OFF + sl * YT_SZ, g_yt + (size_t)((s * NH + h) * 4 + j) * PL, YT_SZ, tfull + sl * 8);
    e_tma3d(sb + ZT_OFF + sl * YT_SZ, zmap, 0, 4 * j, s * 80 + h * 4, tfull + sl * 8);
    e_tma3d(sb + YS_OFF + sl * YS_SZ, ymap, 0, 4 * j, s * 64 + h * 4, tfull + sl * 8);
  };
  auto load_x = [&](int s, int sl) {
    e_expect(tfull + sl * 8, 3 * YT_SZ + 8192);
    e_tma2d(sb + XA_OFF + sl * 8192, xmap, SL * j, s * SEG, tfull + sl * 8);
    e_tma2d(sb + XA_OFF + sl * 8192 + 4096, xmap, SL * j + 64, s * SEG, tfull + sl * 8);
  };
  auto put_w = [&](int s) { e_s2g(g_vt + (size_t)(s * 80 + 64 + h) * PL + SL * j * 8, sb + WT_OFF + (s & 7) * 2048, 1792); };
  auto put_p = [&](int s) { e_s2g(g_p + (size_t)((s * NH + h) * 4 + j) * 320, sb + PS_OFF + (s & 7) * 640, 640); };
  if (v == 2) load_x(0, 0);
  int nl = 2;
  unsigned tf = 0;
  int sl = 2, ph = 1;
  uint32_t yb[14];
  auto load_yb = [&](int sl) {
    const uint32_t ay = sb + YT_OFF + sl * YT_SZ + v * 1792, ap = ay + ((lane & 7) | ((lane & 8) << 1) | ((lane & 16) >> 1)) * 16;
    ldsm4t(ap, yb[0], yb[1], yb[2], yb[3]); ldsm4t(ap + 512, yb[4], yb[5], yb[6], yb[7]);
    ldsm4t(ap + 1024, yb[8], yb[9], yb[10], yb[11]); ldsm2t(ay + 1536 + lane * 16, yb[12], yb[13]);
  };
  load_yb(0);
  for (int s = -1; s < NSEG; s++) {
    OPAQUE(lane);
    const int sn = sl == 2 ? 0 : sl + 1;
    uint32_t aj = sb + MEM_OFF + (lane & 7) * MEM_P + (lane >> 3) * 16 + 224 * v;
    uint4 ov[NOVB];
    #pragma unroll
    for (int i = 0; i < NOVB; i++) ov[i] = lds128(sb + BOV_OFF + (v * NOVB + i) * 512 + lane * 16);
    OPAQUE(aj);
    bar_sync_id(B_PAIR + v, 64);
    TIM(0);
    if (v == 2) { if (s + 2 < NSEG) load_x(s + 2, sl == 0 ? 2 : sl - 1); }
    else if (v == 1) {
      const unsigned late = __ballot_sync(0xffffffffu, tf < TFLAG_N);
      if (__builtin_expect(nl == s + 1 && nl < NSEG, 0)) { load_kv(s + 1, sn, late & 1); nl = s + 2; }
      if (s + 2 < NSEG && !(late & 2)) { load_kv(s + 2, sl == 0 ? 2 : sl - 1, false); nl = s + 3; }
    } else if (v == 0) {
      e_s2g(acc_base() + acc_off(s + 4, j, side) + h * 256, sb + ZER_OFF, 128);
      if (s > 2) { put_w(s - 3); put_p(s - 3); }
      bulk_commit();
    }
    TIM(1);
    uint32_t qa[14];
    ldsm4(aj, qa[0], qa[1], qa[2], qa[3]); ldsm4(aj + 64, qa[4], qa[5], qa[6], qa[7]);
    ldsm4(aj + 128, qa[8], qa[9], qa[10], qa[11]); ldsm2(aj + 192, qa[12], qa[13]);
    const uint32_t zr = lds32(sb + ZER_OFF);
    bar_sync_id(B_PAIR + 4 + v, 64);
    sched_fence();
    {
      float se[4], so[4], te[4], to[4];
      mma16816z(se, qa[0], qa[1], qa[2], qa[3], yb[0], yb[1]); mma16816z(so, qa[0], qa[1], qa[2], qa[3], yb[2], yb[3]);
      mma16816z(te, qa[4], qa[5], qa[6], qa[7], yb[4], yb[5]); mma16816z(to, qa[4], qa[5], qa[6], qa[7], yb[6], yb[7]);
      mma16816(se, qa[8], qa[9], qa[10], qa[11], yb[8], yb[9]); mma16816(so, qa[8], qa[9], qa[10], qa[11], yb[10], yb[11]);
      mma1688(te, qa[12], qa[13], yb[12]); mma1688(to, qa[12], qa[13], yb[13]);
      sts64f(sb + LOC_OFF + v * 256 + lane * 8, ((se[0] + so[2]) + (te[0] + to[2])), ((se[1] + so[3]) + (te[1] + to[3])));
    }
    if (SXL == 2) bar_sync<B_LOC, 256>(); else bar_arrive<B_LOC, 256>();
    sched_fence();
    TIM(2);
    {
      float acc[7][4];
      #pragma unroll
      for (int n = 0; n < 49; n++) {
        const int i = 48 - n, m = i % 7, ks = i / 7, f = i < 49 - NOVB ? i : 0;
        if (VDEP && n == 7 * VDEP) {
          uint32_t t = 0;
          #pragma unroll
          for (int e = 0; e < 7; e++) t |= __float_as_uint(acc[e][0]);
          qa[10 - 2 * VDEP] |= t & zr;
        }
        if (i >= 49 - NOVB) { const uint4 x = ov[i >= 49 - NOVB ? i - (49 - NOVB) : 0]; mma16816z(acc[m], x.x, x.y, x.z, x.w, qa[12], qa[13]); }
        else if (ks == 6) mma16816z(acc[m], bw[f][0], bw[f][1], bw[f][2], bw[f][3], qa[12], qa[13]);
        else mma16816(acc[m], bw[f][0], bw[f][1], bw[f][2], bw[f][3], qa[2 * ks], qa[2 * ks + 1]);
      }
      const uint32_t a = sb + WP_OFF + v * 1792 + lane * 16;
      stsm2(a + 1536, pack_bf(acc[6][0], acc[6][1]), pack_bf(acc[6][2], acc[6][3]));
      #pragma unroll
      for (int mm = 4; mm >= 0; mm -= 2)
        stsm4(a + mm * 256, pack_bf(acc[mm][0], acc[mm][1]), pack_bf(acc[mm][2], acc[mm][3]), pack_bf(acc[mm + 1][0], acc[mm + 1][1]), pack_bf(acc[mm + 1][2], acc[mm + 1][3]));
    }
    bar_arrive<B_W, 256>();
    GTL(h == 1 && j == 1 && v == 0 && s == 0 && lane == 0, 17);
    bar_sync<B_RP, 256>();
    fence_async_smem();
    float e[5][4];
    #pragma unroll
    for (int i = 0; i < 5; i++) e[i][0] = e[i][1] = 0.f;
    if (v == 3 && s >= 0) probs_sum(sb, s - 1, lane, e);
    if (v == 0) { bulk_wait<0>(); red_add_if(lane == 0 && s >= 3, vflag + (s - 3) * 16, 2); }
    const bool landed = mbar_test(tfull + sn * 8, sn ? ph : ph ^ 1);
    TIM(3);
    bar_sync<B_RED, 256>();
    TIM(4);
    {
      float d[32];
      const uint64_t da = mkdesc(sb + XA_OFF + sl * 8192, 16, 512, 1), db = mkdesc(sb + YS_OFF + sl * YS_SZ, 128, 1792, 0);
      wg_fence();
      #pragma unroll
      for (int k = 0; k < 7; k++) { if (k == 0) wg_ss64z<0, 1>(d, da, db); else wg_ss64<0, 1>(d, da + (k >> 2) * 256 + (k & 3) * 2, db + k * 16); }
      wg_commit();
      OPAQUE(lane);
      if (v == 3) probs_fin(sb, s - 1, j, lane, e);
      wg_wait<0>();
      acc_fence<32>(d);
      uint32_t m[5];
      m[0] = pack_bf((d[16] + d[20]) + (d[24] + d[28]), (d[17] + d[21]) + (d[25] + d[29]));
      #pragma unroll
      for (int i = 0; i < 4; i++) m[1 + i] = pack_bf(d[4 * i], d[4 * i + 1]);
      const uint32_t ra = mapa(sb + RX2_OFF + (s & 1) * 2560 + j * 128 + lane * 4, v), rb = mapa(d2t + (s & 1) * 8, v);
      if (v != j) {
        #pragma unroll
        for (int i = 0; i < 5; i++) if (i <= v + 1) st_async32(ra + i * 512, m[i], rb);
      } else {
        #pragma unroll
        for (int i = 0; i < 5; i++) sts32(ra + i * 512, m[i]);
        __syncwarp();
        e_expect(rb, 384 * (j + 2));
      }
    }
    if (__builtin_expect(!landed, 0)) {
      if (s < 0) { cluster_sync_relaxed(); if (v == 1) { load_kv(0, 0, true); load_kv(1, 1, true); } }
      GTL(s < 0 && h == 1 && j == 1 && v == 0 && lane == 0, 20);
      if (s < NSEG - 1) mbar_wait(tfull + sn * 8, sn ? ph : ph ^ 1);
      GTL(s < 0 && h == 1 && j == 1 && v == 0 && lane == 0, 21);
    }
    if (v == 1) tf = ldg_relaxed(tflag + (s + 2 + (lane & 1)) * NH);
    load_yb(sn);
    if (++sl == 3) { sl = 0; ph ^= 1; }
    TIM(5);
  }
  GT(h == 1 && j == 1 && v == 3 && lane == 0, 16);
  if (v == 0) {
    put_w(NSEG - 3); put_w(NSEG - 2); bar_sync<B_END, 160>(); put_w(NSEG - 1);
    bulk_commit(); bulk_wait<0>(); __syncwarp(); red_add_if(lane < 3, vflag + (NSEG - 3 + lane) * 16, 1);
  }
  if (v == 3) {
    fence_async_smem();
    __syncwarp();
    put_p(NSEG - 3); put_p(NSEG - 2); bulk_commit();
    float e[5][4];
    probs_sum(sb, NSEG - 1, lane, e);
    GT(h == 1 && j == 1 && lane == 0 && e[0][0] != 1.2345f, 17);
    probs_fin(sb, NSEG - 1, j, lane, e); fence_async_smem(); __syncwarp();
    GT(h == 1 && j == 1 && lane == 0, 18);
    put_p(NSEG - 1); bulk_commit();
    bulk_wait<1>(); __syncwarp(); red_add_if(lane < 2, vflag + (NSEG - 3 + lane) * 16, 1);
    bulk_wait<0>(); red_add_if(lane == 0, vflag + (NSEG - 1) * 16, 1);
    GT(h == 1 && j == 1 && lane == 0, 6);
  }
}

constexpr int HYS_OFF = 4 * XS_SZ;

#define NFAST 16
#define PWAIT 1300
#define YRF 21
constexpr int NYCL = 14, HOV_OFF = HYS_OFF + 32768;
static_assert(HOV_OFF + 2 * (28 - YRF) * 2048 <= BAR_OFF, "smem");
DEVI void h_keys(const CUtensorMap* xmap, const bf16* x, uint32_t sb, int hid, int r, int side, int warp, int lane) {
  const int wg = warp >> 2, w = warp & 3;
  const uint32_t xfull = sb + BAR_OFF + 24, xempty = sb + BAR_OFF + 56, hov = sb + HOV_OFF + wg * (28 - YRF) * 2048;
  const int u0 = hid * 2, h0 = u0 / 7, h1 = (u0 + 1) / 7;
  auto load_x = [&](int it) {
    if (it >= 2) mbar_wait(xempty + (it & 1) * 8, ((it >> 1) - 1) & 1);
    e_expect(xfull + (it & 1) * 8, 2 * XS_SZ);
    const uint32_t dst = sb + (it & 1) * 2 * XS_SZ + r * 14336;
    const int row = 2 * it * SEG + 16 * r;
    e_tma3d_mc(dst, xmap, 0, row, 0, xfull + (it & 1) * 8, 15);
    e_tma3d_mc(dst + 7168, xmap, 0, row + 8, 0, xfull + (it & 1) * 8, 15);
  };
  if (warp == 7 && hid == 55) asm volatile(ELECT "@pe cp.async.bulk.prefetch.L2.global [%0], 114688;}" :: "l"(x + (size_t)2 * SEG * D) : "memory");
  if (wg) delay_until(clk32() + PWAIT);
  uint32_t a0[28][4], a1[YRF][4];
  const uint4* fr = g_frag[wg] + ((size_t)(u0 * 4 + w) * 28) * 32 + lane;
  auto load_ov = [&]() {
    #pragma unroll
    for (int ks = YRF; ks < 28; ks++) { const uint4 x = fr[(112 + ks) * 32]; stsm4(hov + (ks - YRF) * 2048 + (lane >> 4) * 1024 + w * 256 + (lane & 15) * 16, x.x, x.y, x.z, x.w); }
  };
  auto load_a1 = [&]() {
    #pragma unroll
    for (int ks = 0; ks < YRF; ks++) { const uint4 x = fr[(112 + ks) * 32]; a1[ks][0] = x.x; a1[ks][1] = x.y; a1[ks][2] = x.z; a1[ks][3] = x.w; }
  };
  #pragma unroll
  for (int ks = 0; ks < 28; ks++) { const uint4 x = fr[ks * 32]; a0[ks][0] = x.x; a0[ks][1] = x.y; a0[ks][2] = x.z; a0[ks][3] = x.w; }
  load_ov();
  #pragma unroll
  for (int ks = 0; ks < YRF; ks++) a1[ks][0] = a1[ks][1] = a1[ks][2] = a1[ks][3] = 0;
  bf16* dst0 = (wg ? g_vt : g_yt) + (h0 * 4 + w) * PL + 512 * (u0 - 7 * h0);
  bf16* dst1 = (wg ? g_vt : g_yt) + (h1 * 4 + w) * PL + 512 * (u0 + 1 - 7 * h1);
  const int sstr = (wg ? 80 : 64) * PL;
  GT(hid == 0 && threadIdx.x == 0, 22);
  if (wg == 1) bar_arrive<3, 256>();
  constexpr int NIT = NSEG / 2;
  for (int it = 0; it < NIT; it++) {
    const int s = 2 * it;
    mbar_wait(xfull + (it & 1) * 8, (it >> 1) & 1);
    #pragma unroll
    for (int un = 0; un < 2; un++) {
      float z[32];
      const uint32_t sv = __shfl_sync(0xffffffffu, sb + lds32(sb + BAR_OFF + 124), 0);
      const uint64_t db = mkdesc(sv + (it & 1) * 2 * XS_SZ, 16, 7168, 1), da = mkdesc(hov, 1024, 128, 0);
      bar_sync_id(3 + wg, 256);
      wg_fence();
      #pragma unroll
      for (int ks = 0; ks < 28; ks++) {
        const uint64_t d = db + (ks >> 2) * 64 + (ks & 3) * 2;
        if (ks == 0) wg_rs64z<0>(z, un ? a1[0] : a0[0], d);
        else if (un == 0) wg_rs64<0>(z, a0[ks], d);
        else if (ks < YRF) wg_rs64<0>(z, a1[ks < YRF ? ks : 0], d);
        else wg_ss64<0, 0>(z, da + (ks - YRF) * 128, d);
      }
      wg_commit();
      if (wg == 0 || un == 0 || it < NIT - 1) bar_arrive_id(4 - wg, 256);
      if (un == 0 && it == 0) load_a1();
      wg_wait<0>();
      acc_fence<32>(z);
      OPAQUE(lane);
      const uint32_t st = sb + HYS_OFF + (wg * 2 + un) * 8192, az = st + (lane >> 4) * 1024 + (16 * w + (lane & 15)) * 16;
      #pragma unroll
      for (int i = 0; i < 4; i++) stsm4(az + i * 2048, pack_bf(z[8 * i], z[8 * i + 1]), pack_bf(z[8 * i + 2], z[8 * i + 3]), pack_bf(z[8 * i + 4], z[8 * i + 5]), pack_bf(z[8 * i + 6], z[8 * i + 7]));
      fence_async_smem();
      bulk_wait<0>();
      bar_sync_id(1 + wg, 128);
      bf16* dst = (un ? dst1 : dst0) + (size_t)s * sstr;
      e_s2g(dst, st + w * 1024, 1024);
      e_s2g(dst + sstr, st + 4096 + w * 1024, 1024);
      bulk_commit();
      unsigned* fl = tflag_ptr(side) + (s + lane) * NH;
      if (un == 0) red_add_if(w == 2 && it > NFAST && lane < 2, fl - 2 * NH + h1, 1);
      else {
        red_add_if(w == 2 && lane < 2, fl + h0, 1);
        if (w == 0 && lane < 4) mbar_arrive_remote(mapa(xempty + (it & 1) * 8, lane));
        if (it < NFAST || it == NIT - 1) { bulk_wait<0>(); bar_sync_id(1 + wg, 128); red_add_if(w == 2 && lane < 2, fl + h1, 1); }
        GT(hid == 0 && threadIdx.x == 128 && it == 0, 23);
      }
      __syncwarp();
      if (un == 0 && warp == 1 && it + 1 < NIT) load_x(it + 1);
      if (un == 0 && warp == 7 && hid == it && it + 3 < NIT) asm volatile(ELECT "@pe cp.async.bulk.prefetch.L2.global [%0], 57344;}" :: "l"(x + (size_t)(s + 6) * SEG * D) : "memory");
    }
  }
}

DEVI void store_tile(const float* o, uint32_t st, bf16* dst, int lane) {
  const uint32_t ao = st + (8 * (lane >> 4) + (lane & 7)) * 48 + (lane & 8) * 2;
  stsm4t(ao, pack_bf(o[0], o[1]), pack_bf(o[2], o[3]), pack_bf(o[4], o[5]), pack_bf(o[6], o[7]));
  stsm4t(ao + 16 * 48, pack_bf(o[8], o[9]), pack_bf(o[10], o[11]), pack_bf(o[12], o[13]), pack_bf(o[14], o[15]));
  __syncwarp();
  dst += (size_t)(lane >> 1) * OUTW + 8 * (lane & 1);
  const uint4 u = lds128(st + (lane >> 1) * 48 + (lane & 1) * 16), v = lds128(st + (16 + (lane >> 1)) * 48 + (lane & 1) * 16);
  *(uint4*)dst = u; *(uint4*)(dst + 16 * OUTW) = v;
}
constexpr int F_ST = 28672, F_NS = 5, FP_OFF = F_NS * F_ST, FO_OFF = FP_OFF + 40960, FB_OFF = FO_OFF + 28 * 1536, FIN_SMEM = FB_OFF + 128 + 1024;
template <int WG> DEVI void finish_consume(uint32_t sb, bf16* out, int w, int lane) {
  constexpr int NT = 4 - WG;
  const uint32_t full = sb + FB_OFF, empty = full + 40, pfull = full + 80, pempty = full + 88;
  int par = 0;
  for (int s = blockIdx.x; s < NSEG - NTAIL; s += NFIN, par ^= 1) {
    float o[NT][16];
    mbar_wait(pfull, par);
    const uint32_t sv = __shfl_sync(0xffffffffu, sb + lds32(sb + FB_OFF + 96), 0);
    const uint64_t dv = mkdesc(sv + WG * 4096, 7168, 128, 0), dt = mkdesc(sv + FP_OFF + 128, 128, 640, 0), dm = mkdesc(sv + FP_OFF, 2560, 640, 0);
    #pragma unroll
    for (int i = 0; i < 20; i++) {
      mbar_wait(full + (i % 5) * 8, (i / 5) & 1);
      wg_fence();
      #pragma unroll
      for (int k = 0; k < 2; k++)
        #pragma unroll
        for (int t = 0; t < NT; t++) {
          const uint64_t a = dv + (i % 5) * (F_ST / 16) + t * 64 + k * 896, b = i < 16 ? dt + i * 160 + k * 16 : dm + (i - 16) * 640 + k * 320;
          if (i == 0 && k == 0) wg_ss32z<0, 0>(o[t], a, b); else wg_ss32<0, 0>(o[t], a, b);
        }
      wg_commit();
      if (i > 0) { wg_wait<1>(); e_arrive(empty + ((i - 1) % 5) * 8); }
    }
    wg_wait<0>();
    e_arrive(empty + 32); e_arrive(pempty);
    #pragma unroll
    for (int t = 0; t < NT; t++) { acc_fence<16>(o[t]); store_tile(o[t], sb + FO_OFF + ((WG * 4 + t) * 4 + w) * 1536, out + (size_t)s * SEG * OUTW + D + 64 * (4 * WG + t) + 16 * w, lane); }
    GT(threadIdx.x == 0 && (s & 7) == 7, 208 + (s >> 3));
  }
}
__global__ void __launch_bounds__(288, 1) finish_kernel(bf16* __restrict__ out) {
  extern __shared__ __align__(1024) char smem_raw[];
  const uint32_t sb = (smem_u32(smem_raw) + 1023) & ~1023u;
  const int warp = __shfl_sync(0xffffffffu, threadIdx.x >> 5, 0), lane = threadIdx.x & 31;
  const uint32_t full = sb + FB_OFF, empty = full + 40, pfull = full + 80, pempty = full + 88;
  asm volatile("griddepcontrol.launch_dependents;");
  if (threadIdx.x == 0) {
    for (int i = 0; i < F_NS; i++) { mbar_init(full + i * 8, 1); mbar_init(empty + i * 8, 8); }
    mbar_init(pfull, 1); mbar_init(pempty, 8);
    sts32(sb + FB_OFF + 96, 0);
    asm volatile("fence.mbarrier_init.release.cluster;" ::: "memory");
  }
  __syncthreads();
  if (warp == 8) {
    const int side = rec_side();
    int par = 0;
    for (int s = blockIdx.x; s < NSEG - NTAIL; s += NFIN, par ^= 1) {
      wait_flag(tflag_ptr(side) + s * NH + (lane & 15), TFLAG_N);
      fence_async_global();
      const bf16* src = g_vt + (size_t)s * 80 * PL;
      #pragma unroll 1
      for (int r = 0; r < 4; r++) {
        if (r == 1) {
          wait_flag(vflag_ptr(side) + s * 16, VFLAG_N);
          fence_async_global();
          GT(lane == 0 && (s & 7) == 7, 200 + (s >> 3));
          mbar_wait(pempty, par ^ 1);
          e_expect(pfull, 40960);
          e_g2s(sb + FP_OFF, g_p + (size_t)s * 80 * 256, 40960, pfull);
        }
        #pragma unroll
        for (int i = 0; i < 5; i++, src += 4 * PL) {
          mbar_wait(empty + i * 8, (r & 1) ^ 1);
          e_expect(full + i * 8, F_ST);
          e_g2s(sb + i * F_ST, src, F_ST, full + i * 8);
        }
      }
    }
  } else {
    if (warp < 4) finish_consume<0>(sb, out, warp, lane); else finish_consume<1>(sb, out, warp - 4, lane);
  }
}
constexpr int TP_OFF = 81920, TO_OFF = TP_OFF + 40960, TB_OFF = TO_OFF + 4 * 1536 + 8192, TAIL_SMEM = TB_OFF + 128 + 1024;
__global__ void __launch_bounds__(256, 1) tail_kernel(const __grid_constant__ CUtensorMap vmap, bf16* __restrict__ out) {
  extern __shared__ __align__(1024) char smem_raw[];
  const uint32_t sb = (smem_u32(smem_raw) + 1023) & ~1023u;
  const int warp = __shfl_sync(0xffffffffu, threadIdx.x >> 5, 0), lane = threadIdx.x & 31;
  const int t0 = blockIdx.x % 7, s = NSEG - NTAIL + blockIdx.x / 7, wg = warp >> 2, w = warp & 3;
  const uint32_t bar = sb + TB_OFF;
  if (threadIdx.x == 0) { mbar_init(bar, 1); asm volatile("fence.mbarrier_init.release.cluster;" ::: "memory"); }
  __syncthreads();
  if (warp == 0) {
    const int side = rec_side();
    e_expect(bar, 81920 + 40960);
    wait_flag(tflag_ptr(side) + s * NH + (lane & 15), TFLAG_N);
    fence_async_global();
    for (int i = 0; i < 4; i++) e_tma3d(sb + i * 16384, &vmap, 0, 2 * t0, s * 80 + i * 16, bar);
    wait_flag<40>(vflag_ptr(side) + s * 16, VFLAG_N);
    fence_async_global();
    e_g2s(sb + TP_OFF, g_p + (size_t)s * 80 * 256, 40960, bar);
    e_tma3d(sb + 65536, &vmap, 0, 2 * t0, s * 80 + 64, bar);
    GT(t0 == 0 && lane == 0 && (s & 7) == 7, 200 + (s >> 3));
  }
  float o[16];
  const uint64_t dv = mkdesc(sb + wg * 2048, 1024, 128, 0), dt = mkdesc(sb + TP_OFF + 128 + wg * 256, 128, 640, 0), dm = mkdesc(sb + TP_OFF + wg * 5120, 2560, 640, 0);
  mbar_wait(bar, 0);
  GT(t0 == 0 && threadIdx.x == 32 && s == 63, 20);
  wg_fence();
  #pragma unroll
  for (int i = 0; i < 20; i++) { if (i == 0) wg_ss32z<0, 0>(o, dv, dt); else wg_ss32<0, 0>(o, dv + i * 256, i < 16 ? dt + i * 160 : dm + (i - 16) * 640); }
  wg_commit();
  wg_wait<0>();
  acc_fence<16>(o);
  GT(t0 == 0 && threadIdx.x == 32 && s == 63, 21);
  const uint32_t ex = sb + TO_OFF + 6144 + (w * 32 + lane) * 16;
  if (wg == 1) {
    #pragma unroll
    for (int i = 0; i < 4; i++) sts128(ex + i * 2048, make_uint4(__float_as_uint(o[4 * i]), __float_as_uint(o[4 * i + 1]), __float_as_uint(o[4 * i + 2]), __float_as_uint(o[4 * i + 3])));
  }
  __syncthreads();
  if (wg == 0) {
    #pragma unroll
    for (int i = 0; i < 4; i++) { const uint4 u = lds128(ex + i * 2048); o[4 * i] += __uint_as_float(u.x); o[4 * i + 1] += __uint_as_float(u.y); o[4 * i + 2] += __uint_as_float(u.z); o[4 * i + 3] += __uint_as_float(u.w); }
    store_tile(o, sb + TO_OFF + w * 1536, out + (size_t)s * SEG * OUTW + D + 64 * t0 + 16 * w, lane);
  }
  GT(t0 == 0 && threadIdx.x == 0 && (s & 7) == 7, 208 + (s >> 3));
}

__global__ void __launch_bounds__(256, 1) main_kernel(const __grid_constant__ CUtensorMap xmap, const __grid_constant__ CUtensorMap xmap2,
    const __grid_constant__ CUtensorMap ymap, const __grid_constant__ CUtensorMap zmap, const bf16* __restrict__ x, int role0) {
  extern __shared__ __align__(1024) char smem_raw[];
  const uint32_t sb = (smem_u32(smem_raw) + 1023) & ~1023u;
  const int warp = __shfl_sync(0xffffffffu, threadIdx.x >> 5, 0), lane = threadIdx.x & 31;
  const int r = blockIdx.x & 3;
  GT(blockIdx.x == 5 && threadIdx.x == 0, 2);
  if (threadIdx.x == 0) {
    for (int i = 0; i < 15; i++) mbar_init(sb + BAR_OFF + i * 8, (i >= 7 && i < 11) ? 8 : 1);
    asm volatile("fence.mbarrier_init.release.cluster;" ::: "memory");
  }
  if (threadIdx.x == 32) sts32(sb + BAR_OFF + 124, 0);
  if (threadIdx.x < 32) { sts32(sb + ONES_OFF + threadIdx.x * 4, 0x3f803f80u); sts32(sb + ZER_OFF + threadIdx.x * 4, 0); }
  for (int i = threadIdx.x; i < 1280; i += 256) sts32(sb + RX2_OFF + i * 4, 0);
  fence_async_smem();
  __syncthreads();
  cluster_sync_relaxed();
  uint32_t smid; asm volatile("mov.u32 %0, %%smid;" : "=r"(smid));
  const int myside = tpc_side(min(smid, 155u));
  const int side = rec_side();
  if (r == 0 && threadIdx.x == 0) {
    int role = role0 + (blockIdx.x >> 2);
    if (role0 < 0) {
      if (myside == side) { role = atomicAdd(g_side + 156, 1); if (role >= NH) role = NH + atomicAdd(g_side + 157, 1); }
      else { role = NH + atomicAdd(g_side + 157, 1); if (role >= NH + NYCL) role = atomicAdd(g_side + 156, 1); }
    }
    #pragma unroll
    for (int i = 0; i < 4; i++) asm volatile("st.async.weak.shared::cluster.mbarrier::complete_tx::bytes.u32 [%0], %1, [%2];" :: "r"(mapa(sb + BAR_OFF + 120, i)), "r"(role), "r"(mapa(sb + BAR_OFF + 112, i)) : "memory");
  }
  __syncwarp();
  if (warp == 1) e_expect(sb + BAR_OFF + 112, 4);
  mbar_wait(sb + BAR_OFF + 112, 0);
  const int cl = __shfl_sync(0xffffffffu, lds32(sb + BAR_OFF + 120), 0);
  if (warp == 5 && cl >= NH) {
    e_expect(sb + BAR_OFF + 24, 2 * XS_SZ);
    e_tma3d_mc(sb + r * 14336, &xmap, 0, 16 * r, 0, sb + BAR_OFF + 24, 15);
    e_tma3d_mc(sb + r * 14336 + 7168, &xmap, 0, 16 * r + 8, 0, sb + BAR_OFF + 24, 15);
  }
  asm volatile("griddepcontrol.wait;" ::: "memory");
  GT(blockIdx.x == 5 && threadIdx.x == 0, 19);
  asm volatile("griddepcontrol.launch_dependents;");
  GT(blockIdx.x == 5 && threadIdx.x == 0, 3);
  if (cl < NH) {
    if (warp < 4) {
      asm volatile("pmevent 2;");
      r_score(sb, cl, r, side, warp, lane);
      GT(cl == 1 && r == 1 && threadIdx.x == 0, 4);
    } else {
      asm volatile("pmevent 3;");
      r_value(&xmap2, &ymap, &zmap, sb, cl, r, side, warp, lane);
    }
    cluster_sync_relaxed();
  } else {
    asm volatile("pmevent 4;");
    h_keys(&xmap, x, sb, (cl - NH) * 4 + r, r, side, warp, lane);
    GT(cl == NH && r == 0 && threadIdx.x == 0, 5);
    cluster_sync_relaxed();
  }
}
#define AWAIT 4000
constexpr int A_NEW = 50, A_TILES = (SEQ + A_NEW - 1) / A_NEW, A_NS = 5, A_ST = 10752;
constexpr int AX_OFF = 0, AR_OFF = 61440, AO_P = 240, AO_SZ = 64 * AO_P, AQ_OFF = AR_OFF + 2 * A_NS * A_ST, AQ_P = 400, AQ_SZ = 64 * AQ_P;
constexpr int AB_OFF = AQ_OFF + 2 * AQ_SZ, A_SMEM = AB_OFF + 256 + 1024;
__global__ void __launch_bounds__(384, 1) parta_kernel(const __grid_constant__ CUtensorMap xmap, bf16* __restrict__ out) {
  extern __shared__ __align__(1024) char smem_raw[];
  const uint32_t sb = (smem_u32(smem_raw) + 1023) & ~1023u;
  const int warp = __shfl_sync(0xffffffffu, threadIdx.x >> 5, 0), lane = threadIdx.x & 31;
  const int row0 = (blockIdx.x >> 1) * A_NEW - 14, r = blockIdx.x & 1;
  const uint32_t xbar = sb + AB_OFF + 160, obar = xbar + 8;
  asm volatile("griddepcontrol.launch_dependents;");
  GT(threadIdx.x == 0 && r == 0, 80 + (blockIdx.x >> 1));
  if (threadIdx.x == 0) {
    for (int i = 0; i < 2 * A_NS; i++) { mbar_init(sb + AB_OFF + i * 16, 1); mbar_init(sb + AB_OFF + i * 16 + 8, 4); }
    mbar_init(xbar, 1); mbar_init(obar, 1);
    asm volatile("fence.mbarrier_init.release.cluster;" ::: "memory");
  }
  __syncthreads();
  if (warp >= 8) {
    asm volatile("setmaxnreg.dec.sync.aligned.u32 24;");
    const int wg = warp & 1;
    if (AWAIT && blockIdx.x < 12 - NFIN) delay_until(clk32() + AWAIT);
    if (warp < 10) {
      asm volatile("barrier.cluster.arrive.relaxed.aligned;" ::: "memory");
      const uint32_t bars = sb + AB_OFF + wg * A_NS * 16, ring = sb + AR_OFF + wg * A_NS * A_ST;
      int slot = 0, ph = 1;
      #pragma unroll 1
      for (int p = 0; p < 3; p++) {
        const int sz = p < 2 ? 10752 : 7168;
        const char* src = (const char*)g_aw + (p < 2 ? (4 * r + 2 * p + wg) * 14 * 10752 : D * 168 * 16 + (2 * r + wg) * 14 * 7168);
        #pragma unroll 1
        for (int k = 0; k < 14; k++, src += sz) {
          mbar_wait(bars + slot * 16 + 8, ph);
          e_expect(bars + slot * 16, sz);
          e_g2s(ring + slot * A_ST, src, sz, bars + slot * 16);
          if (++slot == A_NS) { slot = 0; ph ^= 1; }
        }
      }
      asm volatile("barrier.cluster.wait.aligned;" ::: "memory");
    } else if (warp == 10) { e_expect(xbar, 57344); e_tma3d(sb + AX_OFF, &xmap, 0, row0, 0, xbar); e_expect(obar, 2 * A_NEW * AO_P); }
    else if (lane < 14)
      asm volatile("cp.async.bulk.prefetch.L2.global [%0], 28672;" :: "l"((const char*)g_aw + (lane * 4 + (blockIdx.x & 3)) * 28672) : "memory");
  } else {
    asm volatile("setmaxnreg.inc.sync.aligned.u32 240;");
    const int wg = warp >> 2, w = warp & 3, g = lane >> 2, t = lane & 3;
    const uint32_t bars = sb + AB_OFF + wg * A_NS * 16, ring = sb + AR_OFF + wg * A_NS * A_ST, qs = sb + AQ_OFF + wg * AQ_SZ;
    int slot = 0, ph = 0;
    uint32_t a[28][4];
    auto gemm_pass = [&](auto big, float* d) {
      int prev = 0;
      #pragma unroll
      for (int k = 0; k < 14; k++) {
        mbar_wait(bars + slot * 16, ph);
        const uint64_t db = mkdesc(ring + slot * A_ST, 128, 512, 0);
        wg_fence();
        if (big.value) { if (k == 0) wg_rs168z<1>(d, a[0], db); else wg_rs168<1>(d, a[2 * k], db); wg_rs168<1>(d, a[2 * k + 1], db + 16); }
        else { if (k == 0) wg_rs112z<1>(d, a[0], db); else wg_rs112<1>(d, a[2 * k], db); wg_rs112<1>(d, a[2 * k + 1], db + 16); }
        wg_commit();
        if (k > 0) { wg_wait<1>(); e_arrive(bars + prev * 16 + 8); }
        prev = slot;
        if (++slot == A_NS) { slot = 0; ph ^= 1; }
      }
      wg_wait<0>();
      e_arrive(bars + prev * 16 + 8);
    };
    for (int i = w * 32 + lane; i < 384; i += 128) sts64(qs + (i / 6) * AQ_P + (i % 6) * 64 + 56, 0, 0);
    mbar_wait(xbar, 0);
    {
      const int rr = 16 * w + (lane & 15);
      #pragma unroll
      for (int ks = 0; ks < 28; ks++)
        ldsm4(sb + AX_OFF + (ks >> 2) * 8192 + rr * 128 + ((((ks & 3) * 2 + (lane >> 4)) ^ (rr & 7)) << 4), a[ks][0], a[ks][1], a[ks][2], a[ks][3]);
    }
    asm volatile("barrier.cluster.arrive.relaxed.aligned;" ::: "memory");
    #pragma unroll 1
    for (int p = 0; p < 2; p++) {
      {
        float d[84];
        gemm_pass(std::true_type(), d);
        acc_fence<84>(d);
        if (p == 0) asm volatile("barrier.cluster.wait.aligned;" ::: "memory");
        const uint32_t q = qs + ((g & 1) * 32 + 8 * w + (g >> 1)) * AQ_P + 4 * t, q2 = q + (t >= 2 ? 8 : 0);
        #pragma unroll
        for (int nb = 0; nb < 21; nb++) {
          const uint32_t o = (nb % 7 == 3 ? q2 : q) + nb * 16 + (8 * nb / 28) * 8;
          sts32(o, pack_bf(d[4 * nb], d[4 * nb + 1])); sts32(o + 4 * AQ_P, pack_bf(d[4 * nb + 2], d[4 * nb + 3]));
        }
      }
      bar_sync_id(2 + wg, 128);
      {
        const uint32_t hb = qs + (w & 1) * 32 * AQ_P + (w >> 1) * 64;
        float sc[5][4];
        {
          uint32_t qf[2][2][4], kf[4][4];
          #pragma unroll
          for (int i = 0; i < 4; i++) {
            ldsm4(hb + (16 * (i >> 1) + (lane & 15)) * AQ_P + (i & 1) * 32 + (lane >> 4) * 16, qf[i >> 1][i & 1][0], qf[i >> 1][i & 1][1], qf[i >> 1][i & 1][2], qf[i >> 1][i & 1][3]);
            ldsm4(hb + 128 + (8 * i + (lane & 7)) * AQ_P + (lane >> 3) * 16, kf[i][0], kf[i][1], kf[i][2], kf[i][3]);
          }
          #pragma unroll
          for (int i = 0; i < 5; i++) { const int mb = i >= 2, nb = i - mb; mma16816z(sc[i], qf[mb][0][0], qf[mb][0][1], qf[mb][0][2], qf[mb][0][3], kf[nb][0], kf[nb][1]); }
          #pragma unroll
          for (int i = 0; i < 5; i++) { const int mb = i >= 2, nb = i - mb; mma16816(sc[i], qf[mb][1][0], qf[mb][1][1], qf[mb][1][2], qf[mb][1][3], kf[nb][2], kf[nb][3]); }
        }
        uint32_t vf[4][4];
        #pragma unroll
        for (int i = 0; i < 4; i++) ldsm4t(hb + 256 + (8 * i + (lane & 7)) * AQ_P + (lane >> 3) * 16, vf[i][0], vf[i][1], vf[i][2], vf[i][3]);
        const float scl = 0.18898223650461361f * 1.4426950408889634f;
        const int kmin = row0 < 0 ? 7 : 0, dg = g - 2 * t;
        uint32_t pf[5][2];
        float inv[4];
        #pragma unroll
        for (int r = 0; r < 4; r++) {
          const int mb = r >> 1, hf = r & 1, i0 = mb ? 2 : 0, i1 = mb ? 5 : 2;
          float mx = -INFINITY;
          #pragma unroll
          for (int i = i0; i < i1; i++)
            #pragma unroll
            for (int e = 0; e < 2; e++) {
              const int key = 8 * (i - mb) + e, dist = 8 * r - key + dg;
              if (dist < 0 || dist > 7 || (key + 2 * t < kmin && dist != 0)) sc[i][2 * hf + e] = -INFINITY;
              mx = fmaxf(mx, sc[i][2 * hf + e]);
            }
          mx = fmaxf(mx, __shfl_xor_sync(0xffffffffu, mx, 1));
          mx = fmaxf(mx, __shfl_xor_sync(0xffffffffu, mx, 2));
          float den = 0;
          #pragma unroll
          for (int i = i0; i < i1; i++) {
            const float e0 = ex2((sc[i][2 * hf] - mx) * scl), e1 = ex2((sc[i][2 * hf + 1] - mx) * scl);
            den += e0 + e1;
            pf[i][hf] = pack_bf(e0, e1);
          }
          den += __shfl_xor_sync(0xffffffffu, den, 1);
          den += __shfl_xor_sync(0xffffffffu, den, 2);
          inv[r] = rcpf(den);
        }
        const uint32_t ob = sb + AX_OFF + (2 * r + p) * AO_SZ + (2 * g + (w & 1)) * AO_P + (2 * wg + (w >> 1)) * 56 + 4 * t;
        #pragma unroll
        for (int n = 0; n < 4; n++) {
          float o0[4], o1[4];
          mma16816z(o0, pf[0][0], pf[0][1], pf[1][0], pf[1][1], vf[0][n], vf[1][n]);
          mma16816z(o1, pf[3][0], pf[3][1], pf[4][0], pf[4][1], vf[2][n], vf[3][n]);
          mma1688(o1, pf[2][0], pf[2][1], vf[1][n]);
          if (n < 3 || t < 2) {
            sts32(ob + n * 16, pack_bf(o0[0] * inv[0], o0[1] * inv[0])); sts32(ob + 16 * AO_P + n * 16, pack_bf(o0[2] * inv[1], o0[3] * inv[1]));
            sts32(ob + 32 * AO_P + n * 16, pack_bf(o1[0] * inv[2], o1[1] * inv[2])); sts32(ob + 48 * AO_P + n * 16, pack_bf(o1[2] * inv[3], o1[3] * inv[3]));
          }
        }
        __syncwarp();
      }
      fence_async_smem();
      bar_sync<1, 256>();
      if (warp == 0) { const uint32_t src = sb + AX_OFF + (2 * r + p) * AO_SZ + 14 * AO_P; e_s2c(mapa(src, r ^ 1), src, A_NEW * AO_P, mapa(obar, r ^ 1)); }
    }
    mbar_wait(obar, 0);
    asm volatile("barrier.cluster.arrive.relaxed.aligned;" ::: "memory");
    {
      const uint32_t ro = sb + AX_OFF + (16 * w + (lane & 15)) * AO_P + (lane >> 4) * 16;
      #pragma unroll
      for (int ks = 0; ks < 28; ks++) ldsm4(ro + (ks / 7) * AO_SZ + (ks % 7) * 32, a[ks][0], a[ks][1], a[ks][2], a[ks][3]);
      {
        float d[56];
        gemm_pass(std::false_type(), d);
        acc_fence<56>(d);
        const uint32_t st = qs + w * 3840;
        __syncwarp();
        #pragma unroll
        for (int k = 0; k < 7; k++) {
          const int n0 = 2 * k, n1 = 2 * k + 1;
          stsm4(st + (lane & 15) * 240 + (lane >> 4) * 16 + k * 32, pack_bf(d[4 * n0], d[4 * n0 + 1]), pack_bf(d[4 * n0 + 2], d[4 * n0 + 3]), pack_bf(d[4 * n1], d[4 * n1 + 1]), pack_bf(d[4 * n1 + 2], d[4 * n1 + 3]));
        }
        __syncwarp();
        #pragma unroll
        for (int i = 0; i < 7; i++) {
          const int id = i * 32 + lane, rr = id / 14, c = id % 14, tr = 16 * w + rr;
          const uint4 v = lds128(st + rr * 240 + c * 16);
          if (tr >= 14 && row0 + tr < SEQ) *(uint4*)(out + (size_t)(row0 + tr) * OUTW + r * 224 + wg * 112 + c * 8) = v;
        }
      }
    }
    asm volatile("barrier.cluster.wait.aligned;" ::: "memory");
    GT(threadIdx.x == 0 && r == 0, 130 + (blockIdx.x >> 1));
  }
}
typedef CUresult (*EncodeFn)(CUtensorMap*, CUtensorMapDataType, cuuint32_t, void*, const cuuint64_t*, const cuuint64_t*, const cuuint32_t*, const cuuint32_t*,
                             CUtensorMapInterleave, CUtensorMapSwizzle, CUtensorMapL2promotion, CUtensorMapFloatOOBfill);
static void make_map(EncodeFn enc, CUtensorMap* m, const void* p, int rank, cuuint64_t d0, cuuint64_t d1, cuuint64_t d2, cuuint64_t s1, cuuint64_t s2,
                     cuuint32_t b0, cuuint32_t b1, cuuint32_t b2, bool swz, cuuint64_t d3 = 1, cuuint64_t s3 = 0) {
  cuuint64_t gd[4] = {d0, d1, d2, d3}, gs[3] = {s1, s2, s3}; cuuint32_t bx[4] = {b0, b1, b2, 1}, es[4] = {1, 1, 1, 1};
  enc(m, CU_TENSOR_MAP_DATA_TYPE_BFLOAT16, rank, (void*)p, gd, gs, bx, es, CU_TENSOR_MAP_INTERLEAVE_NONE,
      swz ? CU_TENSOR_MAP_SWIZZLE_128B : CU_TENSOR_MAP_SWIZZLE_NONE, CU_TENSOR_MAP_L2_PROMOTION_L2_128B, CU_TENSOR_MAP_FLOAT_OOB_FILL_NONE);
}

extern "C" void kernel_launch(void* const* d_in, const int* in_sizes, int n_in, void* d_out, int out_size) {
  static EncodeFn enc = nullptr;
  static void *kt = nullptr, *yt = nullptr;
  static int ncl = 0;
  cudaLaunchAttribute at[2];
  at[0].id = cudaLaunchAttributeProgrammaticStreamSerialization; at[0].val.programmaticStreamSerializationAllowed = 1;
  at[1].id = cudaLaunchAttributeClusterDimension; at[1].val.clusterDim.x = 4; at[1].val.clusterDim.y = 1; at[1].val.clusterDim.z = 1;
  if (!enc) {
    void* fn = nullptr; cudaDriverEntryPointQueryResult qr;
    cudaGetDriverEntryPoint("cuTensorMapEncodeTiled", &fn, cudaEnableDefault, &qr);
    enc = (EncodeFn)fn;
    cudaFuncSetAttribute(prep_kernel, cudaFuncAttributeMaxDynamicSharedMemorySize, PREP_SMEM);
    cudaFuncSetAttribute(main_kernel, cudaFuncAttributeMaxDynamicSharedMemorySize, MAIN_SMEM);
    cudaFuncSetAttribute(parta_kernel, cudaFuncAttributeMaxDynamicSharedMemorySize, A_SMEM);
    cudaFuncSetAttribute(finish_kernel, cudaFuncAttributeMaxDynamicSharedMemorySize, FIN_SMEM);
    cudaFuncSetAttribute(tail_kernel, cudaFuncAttributeMaxDynamicSharedMemorySize, TAIL_SMEM);
    cudaGetSymbolAddress(&kt, g_vt);
    cudaGetSymbolAddress(&yt, g_yt);
    cudaLaunchConfig_t q = {}; q.gridDim = dim3((NH + NYCL) * 4); q.blockDim = dim3(256); q.dynamicSmemBytes = MAIN_SMEM; q.attrs = at + 1; q.numAttrs = 1;
    cudaOccupancyMaxActiveClusters(&ncl, main_kernel, &q);
  }
  CUtensorMap ax, bx, mq, mk, mv, mo, mz, mvt, my, bx2;
  make_map(enc, &ax, d_in[0], 3, 64, SEQ, 7, 896, 128, 64, 64, 7, true);
  make_map(enc, &bx, d_in[3], 3, 64, SEQ, 7, 896, 128, 64, 8, 7, true);
  make_map(enc, &mq, d_in[5], 3, 64, D, 64, 8192, 128, 64, 64, 4, true);
  make_map(enc, &mk, d_in[6], 3, 64, D, 64, 8192, 128, 64, SL, 4, true);
  make_map(enc, &mv, d_in[7], 3, 64, D, 64, 8192, 128, 64, SL, 4, true);
  make_map(enc, &mo, d_in[8], 2, D, 4096, 1, 896, 0, 64, 256, 1, true);
  make_map(enc, &mz, kt, 3, 224, 16, NSEG * 80, 448, 7168, 224, 4, 4, false);
  make_map(enc, &mvt, kt, 3, 256, 14, NSEG * 80, 512, 7168, 256, 2, 16, false);
  make_map(enc, &my, yt, 3, 224, 16, NSEG * 64, 448, 7168, 224, 4, 4, false);
  make_map(enc, &bx2, d_in[3], 2, D, SEQ, 1, 896, 0, 64, 32, 1, true);
  cudaLaunchConfig_t c = {};
  c.stream = cudaStreamPerThread;
  c.gridDim = dim3(132); c.blockDim = dim3(384); c.dynamicSmemBytes = PREP_SMEM; c.attrs = at; c.numAttrs = 0;
  cudaLaunchKernelEx(&c, prep_kernel, mq, mk, mv, mo, (const uint4*)d_in[1], (const uint4*)d_in[2], (const uint32_t*)d_in[4]);
  c.blockDim = dim3(256); c.dynamicSmemBytes = MAIN_SMEM; c.numAttrs = 2;
  if (ncl >= NH + NYCL) {
    c.gridDim = dim3((NH + NYCL) * 4);
    cudaLaunchKernelEx(&c, main_kernel, bx, bx2, my, mz, (const bf16*)d_in[3], -1);
  } else {
    c.gridDim = dim3(NYCL * 4);
    cudaLaunchKernelEx(&c, main_kernel, bx, bx2, my, mz, (const bf16*)d_in[3], NH);
    c.gridDim = dim3(NH * 4);
    cudaLaunchKernelEx(&c, main_kernel, bx, bx2, my, mz, (const bf16*)d_in[3], 0);
  }
  at[1].val.clusterDim.x = 2;
  c.gridDim = dim3(NFIN); c.blockDim = dim3(288); c.dynamicSmemBytes = FIN_SMEM;
  cudaLaunchKernelEx(&c, finish_kernel, (bf16*)d_out);
  c.gridDim = dim3(2 * A_TILES); c.blockDim = dim3(384); c.dynamicSmemBytes = A_SMEM;
  cudaLaunchKernelEx(&c, parta_kernel, ax, (bf16*)d_out);
  c.numAttrs = 1;
  c.gridDim = dim3(7 * NTAIL); c.blockDim = dim3(256); c.dynamicSmemBytes = TAIL_SMEM;
  cudaLaunchKernelEx(&c, tail_kernel, mvt, (bf16*)d_out);
}
```
